```python
import torch

def _softmax(x, axis=-1):
    return torch.softmax(x, dim=axis)
def _gelu(x):
    return torch.nn.functional.gelu(x, approximate="tanh")
def _silu(x):
    return torch.nn.functional.silu(x)
def _sigmoid(x):
    return torch.sigmoid(x)
def _layernorm(x, axis=-1, eps=1e-5):
    m = x.mean(dim=axis, keepdim=True)
    v = x.var(dim=axis, keepdim=True, unbiased=False)
    return (x - m) / torch.sqrt(v + eps)
def _scatter_add(tgt, idx, src, axis=0):
    return tgt.clone().index_add_(axis, idx, src)
def _segment_sum(src, seg, n):
    out = torch.zeros((n,) + src.shape[1:], dtype=src.dtype)
    return out.index_add_(0, seg, src)
def _pad(x, pw):
    flat = tuple(v for pair in reversed(pw) for v in pair)
    return torch.nn.functional.pad(x, flat)

kernel_name = 'concat_heads__softmax_full_mha__grouped_kv_mqa__prompt'

def setup_inputs():

    _w = (lambda a: (lambda t: t.to(torch.bfloat16) if t.is_floating_point() else t)(torch.as_tensor(a)))
    def _A_setup():
        B, S, D = 1, 2048, 1024
        return {
            "x": _w((lambda *s: torch.randn(*s, dtype=torch.bfloat16) * 0.2)(B, S, D)),
            "wqkv": _w((lambda *s: torch.randn(*s, dtype=torch.bfloat16) * 0.2)(D, 3 * D)),
            "wo": _w((lambda *s: torch.randn(*s, dtype=torch.bfloat16) * 0.05)(D, D)),
        }
    _A_in = _A_setup()

    def _B_setup():
        B, S, D, H = 1, 2048, 1024, 32
        Dh = D // H
        return {
            "x": _w((lambda *s: torch.randn(*s, dtype=torch.bfloat16) * 0.05)(B, S, D)),
            "wq": _w((lambda *s: torch.randn(*s, dtype=torch.bfloat16) * 0.8)(D, H * Dh)),
            "wk": _w((lambda *s: torch.randn(*s, dtype=torch.bfloat16) * 0.8)(D, Dh)),
            "wv": _w((lambda *s: torch.randn(*s, dtype=torch.bfloat16) * 0.1)(D, Dh)),
            "wo": _w((lambda *s: torch.randn(*s, dtype=torch.bfloat16) * 0.1)(H * Dh, D)),
        }
    _B_in = _B_setup()

    return {
        "A_x": _A_in["x"],
        "A_wqkv": _A_in["wqkv"],
        "A_wo": _A_in["wo"],
        "B_x": _B_in["x"],
        "B_wq": _B_in["wq"],
        "B_wk": _B_in["wk"],
        "B_wv": _B_in["wv"],
        "B_wo": _B_in["wo"],
    }

def reference(A_x, A_wqkv, A_wo, B_x, B_wq, B_wk, B_wv, B_wo):
    def _A_ref(x, wqkv, wo):
        B, S, D = x.shape
        H = 32; Dh = D // H
        qkv = (lambda x, *d: x.permute(*d))((x @ wqkv).reshape(B, S, 3, H, Dh), 2, 0, 3, 1, 4)
        q, k, v = qkv[0], qkv[1], qkv[2]
        scale = Dh ** -0.5
        scores = torch.einsum("bhqd,bhkd->bhqk", q, k) * scale
        p = _softmax(scores, axis=-1)
        o = torch.einsum("bhqk,bhkd->bhqd", p, v)
        return (lambda x, *d: x.permute(*d))(o, 0, 2, 1, 3).reshape(B, S, D) @ wo

    def _B_ref(x, wq, wk, wv, wo):
        B, S, D = x.shape
        H = 32
        Dh = D // H
        q = (lambda x, *d: x.permute(*d))((x @ wq).reshape(B, S, H, Dh), 0, 2, 1, 3)
        k = x @ wk
        v = x @ wv
        scores = torch.einsum("bhqd,bkd->bhqk", q, k) * (Dh ** -0.5)
        p = _softmax(scores, axis=-1)
        o = torch.einsum("bhqk,bkd->bhqd", p, v)
        return (lambda x, *d: x.permute(*d))(o, 0, 2, 1, 3).reshape(B, S, H * Dh) @ wo

    a = _A_ref(A_x, A_wqkv, A_wo)
    b = _B_ref(B_x, B_wq, B_wk, B_wv, B_wo)
    return torch.concatenate([a, b], axis=-1)
```

```cpp
#include <cuda_runtime.h>
#include <cuda_bf16.h>
#include <cuda.h>
#include <stdint.h>

namespace {

constexpr int SEQ = 2048;
constexpr int DM = 1024;
constexpr int NSLOT = 130;
constexpr int SLOT_QA = 0, SLOT_KA = 32, SLOT_VA = 64, SLOT_QB = 96, SLOT_KB = 128, SLOT_VB = 129;
constexpr float QSCALE = 0.17677669529663687f * 1.4426950408889634f;

__device__ __align__(1024) __nv_bfloat16 g_qkv[NSLOT * SEQ * 32];
__device__ __align__(1024) __nv_bfloat16 g_o[2 * SEQ * DM];
__device__ __align__(16) float g_n2[NSLOT * 128];

__device__ __forceinline__ uint32_t smem_u32(const void* p) { return (uint32_t)__cvta_generic_to_shared(p); }

__device__ __forceinline__ void mbar_init(uint32_t bar, uint32_t count) {
    asm volatile("mbarrier.init.shared::cta.b64 [%0], %1;" :: "r"(bar), "r"(count) : "memory");
}
__device__ __forceinline__ void mbar_expect_tx(uint32_t bar, uint32_t bytes) {
    asm volatile("mbarrier.arrive.expect_tx.shared::cta.b64 _, [%0], %1;" :: "r"(bar), "r"(bytes) : "memory");
}
__device__ __forceinline__ void mbar_arrive(uint32_t bar) {
    asm volatile("mbarrier.arrive.shared::cta.b64 _, [%0];" :: "r"(bar) : "memory");
}
__device__ __forceinline__ bool mbar_try(uint32_t bar, uint32_t parity) {
    uint32_t ok;
    asm volatile(
        "{\n"
        ".reg .pred p;\n"
        "mbarrier.try_wait.parity.shared::cta.b64 p, [%1], %2;\n"
        "selp.u32 %0, 1, 0, p;\n"
        "}\n" : "=r"(ok) : "r"(bar), "r"(parity) : "memory");
    return ok != 0;
}
__device__ __forceinline__ void mbar_wait(uint32_t bar, uint32_t parity) {
    if (mbar_try(bar, parity)) return;
    const uint32_t t0 = (uint32_t)clock();
    while (!mbar_try(bar, parity)) {
        if ((uint32_t)clock() - t0 > 0x7fffffffu) __trap();
    }
}
__device__ __forceinline__ void fence_barrier_init() { asm volatile("fence.mbarrier_init.release.cluster;" ::: "memory"); }
__device__ __forceinline__ void fence_proxy_async() { asm volatile("fence.proxy.async.shared::cta;" ::: "memory"); }

__device__ __forceinline__ void tma_load_2d(uint32_t dst, const CUtensorMap* map, uint32_t bar, int c0, int c1) {
    asm volatile("cp.async.bulk.tensor.2d.shared::cluster.global.mbarrier::complete_tx::bytes [%0], [%1, {%3, %4}], [%2];"
                 :: "r"(dst), "l"(map), "r"(bar), "r"(c0), "r"(c1) : "memory");
}
__device__ __forceinline__ void tma_load_3d(uint32_t dst, const CUtensorMap* map, uint32_t bar, int c0, int c1, int c2) {
    asm volatile("cp.async.bulk.tensor.3d.shared::cluster.global.mbarrier::complete_tx::bytes [%0], [%1, {%3, %4, %5}], [%2];"
                 :: "r"(dst), "l"(map), "r"(bar), "r"(c0), "r"(c1), "r"(c2) : "memory");
}
__device__ __forceinline__ void tma_store_2d(const CUtensorMap* map, uint32_t src, int c0, int c1) {
    asm volatile("cp.async.bulk.tensor.2d.global.shared::cta.bulk_group [%0, {%2, %3}], [%1];"
                 :: "l"(map), "r"(src), "r"(c0), "r"(c1) : "memory");
}
__device__ __forceinline__ void tma_store_3d(const CUtensorMap* map, uint32_t src, int c0, int c1, int c2) {
    asm volatile("cp.async.bulk.tensor.3d.global.shared::cta.bulk_group [%0, {%2, %3, %4}], [%1];"
                 :: "l"(map), "r"(src), "r"(c0), "r"(c1), "r"(c2) : "memory");
}
__device__ __forceinline__ void bulk_commit() { asm volatile("cp.async.bulk.commit_group;" ::: "memory"); }
template <int N> __device__ __forceinline__ void bulk_wait_read() { asm volatile("cp.async.bulk.wait_group.read %0;" :: "n"(N) : "memory"); }
template <int N> __device__ __forceinline__ void bulk_wait() { asm volatile("cp.async.bulk.wait_group %0;" :: "n"(N) : "memory"); }
__device__ __forceinline__ void prefetch_map(const CUtensorMap* map) {
    asm volatile("prefetch.tensormap [%0];" :: "l"(map) : "memory");
}
__device__ __forceinline__ void pdl_wait() { asm volatile("griddepcontrol.wait;" ::: "memory"); }
__device__ __forceinline__ void pdl_launch() { asm volatile("griddepcontrol.launch_dependents;" ::: "memory"); }

__device__ __forceinline__ void wg_fence() { asm volatile("wgmma.fence.sync.aligned;" ::: "memory"); }
__device__ __forceinline__ void wg_commit() { asm volatile("wgmma.commit_group.sync.aligned;" ::: "memory"); }
template <int N> __device__ __forceinline__ void wg_wait() { asm volatile("wgmma.wait_group.sync.aligned %0;" :: "n"(N) : "memory"); }
template <int N> __device__ __forceinline__ void fence_regs(float (&r)[N]) {
#pragma unroll
    for (int i = 0; i < N; i++) asm volatile("" : "+f"(r[i]) :: "memory");
}

template <int N> __device__ __forceinline__ void reg_alloc() { asm volatile("setmaxnreg.inc.sync.aligned.u32 %0;" :: "n"(N)); }
template <int N> __device__ __forceinline__ void reg_dealloc() { asm volatile("setmaxnreg.dec.sync.aligned.u32 %0;" :: "n"(N)); }
__device__ __forceinline__ void named_bar_sync(int id, int n) { asm volatile("bar.sync %0, %1;" :: "r"(id), "r"(n) : "memory"); }

__device__ __forceinline__ uint32_t pack_bf16(float lo, float hi) {
    uint32_t r;
    asm("cvt.rn.bf16x2.f32 %0, %1, %2;" : "=r"(r) : "f"(hi), "f"(lo));
    return r;
}
__device__ __forceinline__ void stmatrix_x4(uint32_t addr, uint32_t r0, uint32_t r1, uint32_t r2, uint32_t r3) {
    asm volatile("stmatrix.sync.aligned.m8n8.x4.shared.b16 [%0], {%1, %2, %3, %4};"
                 :: "r"(addr), "r"(r0), "r"(r1), "r"(r2), "r"(r3) : "memory");
}
__device__ __forceinline__ void ldmatrix_x4(uint32_t addr, uint32_t (&r)[4]) {
    asm volatile("ldmatrix.sync.aligned.m8n8.x4.shared.b16 {%0, %1, %2, %3}, [%4];"
                 : "=r"(r[0]), "=r"(r[1]), "=r"(r[2]), "=r"(r[3]) : "r"(addr) : "memory");
}
__device__ __forceinline__ float ex2_mufu(float x) {
    float y;
    asm("ex2.approx.ftz.f32 %0, %1;" : "=f"(y) : "f"(x));
    return y;
}
__device__ __forceinline__ float ex2_poly(float x) {
    const float magic = 12582912.0f;
    float t = __fadd_rn(x, magic);
    float r = __fadd_rn(t, -magic);
    float f = __fadd_rn(x, -r);
    float p = fmaf(0.0551716685295105f, f, 0.2426111251115799f);
    p = fmaf(p, f, 0.6932609677314758f);
    p = fmaf(p, f, 0.9999280571937561f);
    return __uint_as_float(__float_as_uint(p) + (__float_as_uint(t) << 23));
}

__device__ __forceinline__ uint64_t make_desc(uint32_t addr, uint32_t lbo, uint32_t sbo, uint32_t swz) {
    return (uint64_t)((addr & 0x3FFFF) >> 4) | ((uint64_t)((lbo >> 4) & 0x3FFF) << 16) |
           ((uint64_t)((sbo >> 4) & 0x3FFF) << 32) | ((uint64_t)swz << 62);
}

__device__ __forceinline__ void wgmma_ss_n256_tb(float (&d)[128], uint64_t descA, uint64_t descB) {
    asm volatile(
        "wgmma.mma_async.sync.aligned.m64n256k16.f32.bf16.bf16 "
        "{%0, %1, %2, %3, %4, %5, %6, %7, %8, %9, %10, %11, %12, %13, %14, %15, "
        "%16, %17, %18, %19, %20, %21, %22, %23, %24, %25, %26, %27, %28, %29, %30, %31, "
        "%32, %33, %34, %35, %36, %37, %38, %39, %40, %41, %42, %43, %44, %45, %46, %47, "
        "%48, %49, %50, %51, %52, %53, %54, %55, %56, %57, %58, %59, %60, %61, %62, %63, "
        "%64, %65, %66, %67, %68, %69, %70, %71, %72, %73, %74, %75, %76, %77, %78, %79, "
        "%80, %81, %82, %83, %84, %85, %86, %87, %88, %89, %90, %91, %92, %93, %94, %95, "
        "%96, %97, %98, %99, %100, %101, %102, %103, %104, %105, %106, %107, %108, %109, %110, %111, "
        "%112, %113, %114, %115, %116, %117, %118, %119, %120, %121, %122, %123, %124, %125, %126, %127}, "
        "%128, %129, 1, 1, 1, 0, 1;\n"
        : "+f"(d[0]), "+f"(d[1]), "+f"(d[2]), "+f"(d[3]), "+f"(d[4]), "+f"(d[5]), "+f"(d[6]), "+f"(d[7]),
          "+f"(d[8]), "+f"(d[9]), "+f"(d[10]), "+f"(d[11]), "+f"(d[12]), "+f"(d[13]), "+f"(d[14]), "+f"(d[15]),
          "+f"(d[16]), "+f"(d[17]), "+f"(d[18]), "+f"(d[19]), "+f"(d[20]), "+f"(d[21]), "+f"(d[22]), "+f"(d[23]),
          "+f"(d[24]), "+f"(d[25]), "+f"(d[26]), "+f"(d[27]), "+f"(d[28]), "+f"(d[29]), "+f"(d[30]), "+f"(d[31]),
          "+f"(d[32]), "+f"(d[33]), "+f"(d[34]), "+f"(d[35]), "+f"(d[36]), "+f"(d[37]), "+f"(d[38]), "+f"(d[39]),
          "+f"(d[40]), "+f"(d[41]), "+f"(d[42]), "+f"(d[43]), "+f"(d[44]), "+f"(d[45]), "+f"(d[46]), "+f"(d[47]),
          "+f"(d[48]), "+f"(d[49]), "+f"(d[50]), "+f"(d[51]), "+f"(d[52]), "+f"(d[53]), "+f"(d[54]), "+f"(d[55]),
          "+f"(d[56]), "+f"(d[57]), "+f"(d[58]), "+f"(d[59]), "+f"(d[60]), "+f"(d[61]), "+f"(d[62]), "+f"(d[63]),
          "+f"(d[64]), "+f"(d[65]), "+f"(d[66]), "+f"(d[67]), "+f"(d[68]), "+f"(d[69]), "+f"(d[70]), "+f"(d[71]),
          "+f"(d[72]), "+f"(d[73]), "+f"(d[74]), "+f"(d[75]), "+f"(d[76]), "+f"(d[77]), "+f"(d[78]), "+f"(d[79]),
          "+f"(d[80]), "+f"(d[81]), "+f"(d[82]), "+f"(d[83]), "+f"(d[84]), "+f"(d[85]), "+f"(d[86]), "+f"(d[87]),
          "+f"(d[88]), "+f"(d[89]), "+f"(d[90]), "+f"(d[91]), "+f"(d[92]), "+f"(d[93]), "+f"(d[94]), "+f"(d[95]),
          "+f"(d[96]), "+f"(d[97]), "+f"(d[98]), "+f"(d[99]), "+f"(d[100]), "+f"(d[101]), "+f"(d[102]), "+f"(d[103]),
          "+f"(d[104]), "+f"(d[105]), "+f"(d[106]), "+f"(d[107]), "+f"(d[108]), "+f"(d[109]), "+f"(d[110]), "+f"(d[111]),
          "+f"(d[112]), "+f"(d[113]), "+f"(d[114]), "+f"(d[115]), "+f"(d[116]), "+f"(d[117]), "+f"(d[118]), "+f"(d[119]),
          "+f"(d[120]), "+f"(d[121]), "+f"(d[122]), "+f"(d[123]), "+f"(d[124]), "+f"(d[125]), "+f"(d[126]), "+f"(d[127])
        : "l"(descA), "l"(descB));
}
__device__ __forceinline__ void wgmma_ss_n256_tb_z(float (&d)[128], uint64_t descA, uint64_t descB) {
    asm volatile(
        "wgmma.mma_async.sync.aligned.m64n256k16.f32.bf16.bf16 "
        "{%0, %1, %2, %3, %4, %5, %6, %7, %8, %9, %10, %11, %12, %13, %14, %15, "
        "%16, %17, %18, %19, %20, %21, %22, %23, %24, %25, %26, %27, %28, %29, %30, %31, "
        "%32, %33, %34, %35, %36, %37, %38, %39, %40, %41, %42, %43, %44, %45, %46, %47, "
        "%48, %49, %50, %51, %52, %53, %54, %55, %56, %57, %58, %59, %60, %61, %62, %63, "
        "%64, %65, %66, %67, %68, %69, %70, %71, %72, %73, %74, %75, %76, %77, %78, %79, "
        "%80, %81, %82, %83, %84, %85, %86, %87, %88, %89, %90, %91, %92, %93, %94, %95, "
        "%96, %97, %98, %99, %100, %101, %102, %103, %104, %105, %106, %107, %108, %109, %110, %111, "
        "%112, %113, %114, %115, %116, %117, %118, %119, %120, %121, %122, %123, %124, %125, %126, %127}, "
        "%128, %129, 0, 1, 1, 0, 1;\n"
        : "=f"(d[0]), "=f"(d[1]), "=f"(d[2]), "=f"(d[3]), "=f"(d[4]), "=f"(d[5]), "=f"(d[6]), "=f"(d[7]),
          "=f"(d[8]), "=f"(d[9]), "=f"(d[10]), "=f"(d[11]), "=f"(d[12]), "=f"(d[13]), "=f"(d[14]), "=f"(d[15]),
          "=f"(d[16]), "=f"(d[17]), "=f"(d[18]), "=f"(d[19]), "=f"(d[20]), "=f"(d[21]), "=f"(d[22]), "=f"(d[23]),
          "=f"(d[24]), "=f"(d[25]), "=f"(d[26]), "=f"(d[27]), "=f"(d[28]), "=f"(d[29]), "=f"(d[30]), "=f"(d[31]),
          "=f"(d[32]), "=f"(d[33]), "=f"(d[34]), "=f"(d[35]), "=f"(d[36]), "=f"(d[37]), "=f"(d[38]), "=f"(d[39]),
          "=f"(d[40]), "=f"(d[41]), "=f"(d[42]), "=f"(d[43]), "=f"(d[44]), "=f"(d[45]), "=f"(d[46]), "=f"(d[47]),
          "=f"(d[48]), "=f"(d[49]), "=f"(d[50]), "=f"(d[51]), "=f"(d[52]), "=f"(d[53]), "=f"(d[54]), "=f"(d[55]),
          "=f"(d[56]), "=f"(d[57]), "=f"(d[58]), "=f"(d[59]), "=f"(d[60]), "=f"(d[61]), "=f"(d[62]), "=f"(d[63]),
          "=f"(d[64]), "=f"(d[65]), "=f"(d[66]), "=f"(d[67]), "=f"(d[68]), "=f"(d[69]), "=f"(d[70]), "=f"(d[71]),
          "=f"(d[72]), "=f"(d[73]), "=f"(d[74]), "=f"(d[75]), "=f"(d[76]), "=f"(d[77]), "=f"(d[78]), "=f"(d[79]),
          "=f"(d[80]), "=f"(d[81]), "=f"(d[82]), "=f"(d[83]), "=f"(d[84]), "=f"(d[85]), "=f"(d[86]), "=f"(d[87]),
          "=f"(d[88]), "=f"(d[89]), "=f"(d[90]), "=f"(d[91]), "=f"(d[92]), "=f"(d[93]), "=f"(d[94]), "=f"(d[95]),
          "=f"(d[96]), "=f"(d[97]), "=f"(d[98]), "=f"(d[99]), "=f"(d[100]), "=f"(d[101]), "=f"(d[102]), "=f"(d[103]),
          "=f"(d[104]), "=f"(d[105]), "=f"(d[106]), "=f"(d[107]), "=f"(d[108]), "=f"(d[109]), "=f"(d[110]), "=f"(d[111]),
          "=f"(d[112]), "=f"(d[113]), "=f"(d[114]), "=f"(d[115]), "=f"(d[116]), "=f"(d[117]), "=f"(d[118]), "=f"(d[119]),
          "=f"(d[120]), "=f"(d[121]), "=f"(d[122]), "=f"(d[123]), "=f"(d[124]), "=f"(d[125]), "=f"(d[126]), "=f"(d[127])
        : "l"(descA), "l"(descB));
}
__device__ __forceinline__ void wgmma_ss_n64_tb(float (&d)[32], uint64_t descA, uint64_t descB) {
    asm volatile(
        "wgmma.mma_async.sync.aligned.m64n64k16.f32.bf16.bf16 "
        "{%0, %1, %2, %3, %4, %5, %6, %7, %8, %9, %10, %11, %12, %13, %14, %15, "
        "%16, %17, %18, %19, %20, %21, %22, %23, %24, %25, %26, %27, %28, %29, %30, %31}, "
        "%32, %33, 1, 1, 1, 0, 1;\n"
        : "+f"(d[0]), "+f"(d[1]), "+f"(d[2]), "+f"(d[3]), "+f"(d[4]), "+f"(d[5]), "+f"(d[6]), "+f"(d[7]),
          "+f"(d[8]), "+f"(d[9]), "+f"(d[10]), "+f"(d[11]), "+f"(d[12]), "+f"(d[13]), "+f"(d[14]), "+f"(d[15]),
          "+f"(d[16]), "+f"(d[17]), "+f"(d[18]), "+f"(d[19]), "+f"(d[20]), "+f"(d[21]), "+f"(d[22]), "+f"(d[23]),
          "+f"(d[24]), "+f"(d[25]), "+f"(d[26]), "+f"(d[27]), "+f"(d[28]), "+f"(d[29]), "+f"(d[30]), "+f"(d[31])
        : "l"(descA), "l"(descB));
}
__device__ __forceinline__ void wgmma_ss_n64_tb_z(float (&d)[32], uint64_t descA, uint64_t descB) {
    asm volatile(
        "wgmma.mma_async.sync.aligned.m64n64k16.f32.bf16.bf16 "
        "{%0, %1, %2, %3, %4, %5, %6, %7, %8, %9, %10, %11, %12, %13, %14, %15, "
        "%16, %17, %18, %19, %20, %21, %22, %23, %24, %25, %26, %27, %28, %29, %30, %31}, "
        "%32, %33, 0, 1, 1, 0, 1;\n"
        : "=f"(d[0]), "=f"(d[1]), "=f"(d[2]), "=f"(d[3]), "=f"(d[4]), "=f"(d[5]), "=f"(d[6]), "=f"(d[7]),
          "=f"(d[8]), "=f"(d[9]), "=f"(d[10]), "=f"(d[11]), "=f"(d[12]), "=f"(d[13]), "=f"(d[14]), "=f"(d[15]),
          "=f"(d[16]), "=f"(d[17]), "=f"(d[18]), "=f"(d[19]), "=f"(d[20]), "=f"(d[21]), "=f"(d[22]), "=f"(d[23]),
          "=f"(d[24]), "=f"(d[25]), "=f"(d[26]), "=f"(d[27]), "=f"(d[28]), "=f"(d[29]), "=f"(d[30]), "=f"(d[31])
        : "l"(descA), "l"(descB));
}
__device__ __forceinline__ void wgmma_rs_n64(float (&d)[32], const uint32_t (&a)[4], uint64_t descB) {
    asm volatile(
        "wgmma.mma_async.sync.aligned.m64n64k16.f32.bf16.bf16 "
        "{%0, %1, %2, %3, %4, %5, %6, %7, %8, %9, %10, %11, %12, %13, %14, %15, "
        "%16, %17, %18, %19, %20, %21, %22, %23, %24, %25, %26, %27, %28, %29, %30, %31}, "
        "{%32, %33, %34, %35}, %36, 1, 1, 1, 0;\n"
        : "+f"(d[0]), "+f"(d[1]), "+f"(d[2]), "+f"(d[3]), "+f"(d[4]), "+f"(d[5]), "+f"(d[6]), "+f"(d[7]),
          "+f"(d[8]), "+f"(d[9]), "+f"(d[10]), "+f"(d[11]), "+f"(d[12]), "+f"(d[13]), "+f"(d[14]), "+f"(d[15]),
          "+f"(d[16]), "+f"(d[17]), "+f"(d[18]), "+f"(d[19]), "+f"(d[20]), "+f"(d[21]), "+f"(d[22]), "+f"(d[23]),
          "+f"(d[24]), "+f"(d[25]), "+f"(d[26]), "+f"(d[27]), "+f"(d[28]), "+f"(d[29]), "+f"(d[30]), "+f"(d[31])
        : "r"(a[0]), "r"(a[1]), "r"(a[2]), "r"(a[3]), "l"(descB));
}
__device__ __forceinline__ void wgmma_rs_n64_z(float (&d)[32], const uint32_t (&a)[4], uint64_t descB) {
    asm volatile(
        "wgmma.mma_async.sync.aligned.m64n64k16.f32.bf16.bf16 "
        "{%0, %1, %2, %3, %4, %5, %6, %7, %8, %9, %10, %11, %12, %13, %14, %15, "
        "%16, %17, %18, %19, %20, %21, %22, %23, %24, %25, %26, %27, %28, %29, %30, %31}, "
        "{%32, %33, %34, %35}, %36, 0, 1, 1, 0;\n"
        : "=f"(d[0]), "=f"(d[1]), "=f"(d[2]), "=f"(d[3]), "=f"(d[4]), "=f"(d[5]), "=f"(d[6]), "=f"(d[7]),
          "=f"(d[8]), "=f"(d[9]), "=f"(d[10]), "=f"(d[11]), "=f"(d[12]), "=f"(d[13]), "=f"(d[14]), "=f"(d[15]),
          "=f"(d[16]), "=f"(d[17]), "=f"(d[18]), "=f"(d[19]), "=f"(d[20]), "=f"(d[21]), "=f"(d[22]), "=f"(d[23]),
          "=f"(d[24]), "=f"(d[25]), "=f"(d[26]), "=f"(d[27]), "=f"(d[28]), "=f"(d[29]), "=f"(d[30]), "=f"(d[31])
        : "r"(a[0]), "r"(a[1]), "r"(a[2]), "r"(a[3]), "l"(descB));
}
__device__ __forceinline__ void wgmma_rs_n40_tb(float (&d)[20], const uint32_t (&a)[4], uint64_t descB) {
    asm volatile(
        "wgmma.mma_async.sync.aligned.m64n40k16.f32.bf16.bf16 "
        "{%0, %1, %2, %3, %4, %5, %6, %7, %8, %9, %10, %11, %12, %13, %14, %15, "
        "%16, %17, %18, %19}, "
        "{%20, %21, %22, %23}, %24, 1, 1, 1, 1;\n"
        : "+f"(d[0]), "+f"(d[1]), "+f"(d[2]), "+f"(d[3]), "+f"(d[4]), "+f"(d[5]), "+f"(d[6]), "+f"(d[7]),
          "+f"(d[8]), "+f"(d[9]), "+f"(d[10]), "+f"(d[11]), "+f"(d[12]), "+f"(d[13]), "+f"(d[14]), "+f"(d[15]),
          "+f"(d[16]), "+f"(d[17]), "+f"(d[18]), "+f"(d[19])
        : "r"(a[0]), "r"(a[1]), "r"(a[2]), "r"(a[3]), "l"(descB));
}

constexpr int G_STAGES = 4;
constexpr int G_A_BYTES = 128 * 64 * 2;
constexpr int G_B_BYTES = 64 * 256 * 2;
constexpr int G_STAGE_BYTES = G_A_BYTES + G_B_BYTES;
constexpr int G_EPI_BYTES = 32768;
constexpr int G_SMEM = 1024 + G_STAGES * G_STAGE_BYTES + G_EPI_BYTES + 256;
constexpr int G_THREADS = 384;

struct ProjParams {
    CUtensorMap xa, xb, wqkv, wq, wk, wv, qkv_st;
};
struct OutParams {
    CUtensorMap o, woa, wob, out_st;
};

__device__ __forceinline__ void slot_norm(const float* v, int slot, int grp16, int lane) {
    float a = 0.f, b = 0.f;
#pragma unroll
    for (int j = 0; j < 4; j++) {
        a = fmaf(v[4 * j + 0], v[4 * j + 0], a);
        a = fmaf(v[4 * j + 1], v[4 * j + 1], a);
        b = fmaf(v[4 * j + 2], v[4 * j + 2], b);
        b = fmaf(v[4 * j + 3], v[4 * j + 3], b);
    }
    a += __shfl_xor_sync(0xffffffffu, a, 1);
    b += __shfl_xor_sync(0xffffffffu, b, 1);
    a += __shfl_xor_sync(0xffffffffu, a, 2);
    b += __shfl_xor_sync(0xffffffffu, b, 2);
    uint32_t m = max(__float_as_uint(a) & 0x7fffffffu, __float_as_uint(b) & 0x7fffffffu);
    m = __reduce_max_sync(0xffffffffu, m);
    if (lane == 0) g_n2[slot * 128 + grp16] = __uint_as_float(m);
}

__global__ void __launch_bounds__(G_THREADS, 1) proj_kernel(const __grid_constant__ ProjParams P) {
    extern __shared__ uint8_t smem_raw[];
    const uint32_t sbase = (smem_u32(smem_raw) + 1023u) & ~1023u;
    const uint32_t s_epi = sbase + G_STAGES * G_STAGE_BYTES;
    const uint32_t s_bar = s_epi + G_EPI_BYTES;
    const int tid = threadIdx.x, warp = tid >> 5, lane = tid & 31;
    const int cta = blockIdx.x;

    if (tid == 0) {
        for (int s = 0; s < G_STAGES; s++) { mbar_init(s_bar + s * 8, 1); mbar_init(s_bar + 32 + s * 8, 8); }
        fence_barrier_init();
    }
    __syncthreads();
    pdl_launch();

    const bool kvcta = cta >= 128;
    const int ntiles = kvcta ? 4 : 2;

    if (warp >= 8) {
        reg_dealloc<40>();
        if (warp == 8 && lane == 0) {
            int stage = 0; uint32_t phase = 1;
            for (int it = 0; it < ntiles; it++) {
                if (!kvcta) {
                    const int u = cta + 128 * it;
                    const bool isA = u < 192;
                    const int v = isA ? u : u - 192;
                    const int mblk = v & 15, nblk = v >> 4;
                    const CUtensorMap* ma = isA ? &P.xa : &P.xb;
                    const CUtensorMap* mb = isA ? &P.wqkv : &P.wq;
                    for (int kb = 0; kb < 16; kb++) {
                        mbar_wait(s_bar + 32 + stage * 8, phase);
                        const uint32_t full = s_bar + stage * 8;
                        mbar_expect_tx(full, G_STAGE_BYTES);
                        const uint32_t sa = sbase + stage * G_STAGE_BYTES;
                        tma_load_2d(sa, ma, full, kb * 64, mblk * 128);
                        tma_load_3d(sa + G_A_BYTES, mb, full, 0, kb * 64, nblk * 4);
                        if (++stage == G_STAGES) { stage = 0; phase ^= 1; }
                    }
                } else {
                    const int mblk = (cta - 128) * 4 + it;
                    for (int kb = 0; kb < 16; kb++) {
                        mbar_wait(s_bar + 32 + stage * 8, phase);
                        const uint32_t full = s_bar + stage * 8;
                        mbar_expect_tx(full, G_A_BYTES + 8192);
                        const uint32_t sa = sbase + stage * G_STAGE_BYTES;
                        tma_load_2d(sa, &P.xb, full, kb * 64, mblk * 128);
                        tma_load_2d(sa + G_A_BYTES, &P.wk, full, 0, kb * 64);
                        tma_load_2d(sa + G_A_BYTES + 4096, &P.wv, full, 0, kb * 64);
                        if (++stage == G_STAGES) { stage = 0; phase ^= 1; }
                    }
                }
            }
        }
    } else {
        reg_alloc<232>();
        const int wg = warp >> 2, wq = warp & 3;
        int stage = 0; uint32_t phase = 0;
        const uint32_t epi = s_epi + wg * 16384;
        const int srow = wq * 16 + (lane & 7);
        const uint32_t st_off0 = srow * 64 + (((lane >> 3) ^ ((srow >> 1) & 3)) << 4);
        const uint32_t st_off1 = (srow + 8) * 64 + (((lane >> 3) ^ (((srow + 8) >> 1) & 3)) << 4);
        for (int it = 0; it < ntiles; it++) {
            if (!kvcta) {
                const int u = cta + 128 * it;
                const bool isA = u < 192;
                const int v = isA ? u : u - 192;
                const int mblk = v & 15, nblk = v >> 4;
                const int slot0 = (isA ? 0 : SLOT_QB) + nblk * 8;
                float acc[128];
#pragma unroll
                for (int i = 0; i < 128; i++) acc[i] = 0.f;
                for (int kb = 0; kb < 16; kb++) {
                    mbar_wait(s_bar + stage * 8, phase);
                    const uint32_t sa = sbase + stage * G_STAGE_BYTES;
                    const uint64_t da = make_desc(sa + wg * 8192, 16, 1024, 1);
                    const uint64_t db = make_desc(sa + G_A_BYTES, 8192, 1024, 1);
                    wg_fence();
#pragma unroll
                    for (int kk = 0; kk < 4; kk++) wgmma_ss_n256_tb(acc, da + kk * 2, db + kk * 128);
                    wg_commit();
                    if (kb > 0) {
                        wg_wait<1>();
                        if (lane == 0) mbar_arrive(s_bar + 32 + ((stage + G_STAGES - 1) % G_STAGES) * 8);
                    }
                    if (++stage == G_STAGES) { stage = 0; phase ^= 1; }
                }
                wg_wait<0>();
                fence_regs(acc);
                if (lane == 0) mbar_arrive(s_bar + 32 + ((stage + G_STAGES - 1) % G_STAGES) * 8);
                const bool isQ = slot0 < SLOT_KA || slot0 >= SLOT_QB;
                const bool isK = slot0 >= SLOT_KA && slot0 < SLOT_QB;
                const float sc = isQ ? QSCALE : 1.0f;
                const int row0 = mblk * 128 + wg * 64;
#pragma unroll
                for (int half = 0; half < 2; half++) {
                    if (wq == 0 && lane == 0) bulk_wait_read<0>();
                    named_bar_sync(1 + wg, 128);
#pragma unroll
                    for (int s = 0; s < 4; s++) {
                        const float* v16 = &acc[(half * 4 + s) * 16];
                        if (isK) slot_norm(v16, slot0 + half * 4 + s, (row0 >> 4) + wq, lane);
                        stmatrix_x4(epi + s * 4096 + st_off0,
                                    pack_bf16(v16[0] * sc, v16[1] * sc), pack_bf16(v16[4] * sc, v16[5] * sc),
                                    pack_bf16(v16[8] * sc, v16[9] * sc), pack_bf16(v16[12] * sc, v16[13] * sc));
                        stmatrix_x4(epi + s * 4096 + st_off1,
                                    pack_bf16(v16[2] * sc, v16[3] * sc), pack_bf16(v16[6] * sc, v16[7] * sc),
                                    pack_bf16(v16[10] * sc, v16[11] * sc), pack_bf16(v16[14] * sc, v16[15] * sc));
                    }
                    fence_proxy_async();
                    named_bar_sync(1 + wg, 128);
                    if (wq == 0 && lane == 0) {
                        tma_store_3d(&P.qkv_st, epi, 0, row0, slot0 + half * 4);
                        bulk_commit();
                    }
                }
            } else {
                const int mblk = (cta - 128) * 4 + it;
                float acc[32];
#pragma unroll
                for (int i = 0; i < 32; i++) acc[i] = 0.f;
                for (int kb = 0; kb < 16; kb++) {
                    mbar_wait(s_bar + stage * 8, phase);
                    const uint32_t sa = sbase + stage * G_STAGE_BYTES;
                    const uint64_t da = make_desc(sa + wg * 8192, 16, 1024, 1);
                    const uint64_t db = make_desc(sa + G_A_BYTES, 4096, 512, 2);
                    wg_fence();
#pragma unroll
                    for (int kk = 0; kk < 4; kk++) wgmma_ss_n64_tb(acc, da + kk * 2, db + kk * 64);
                    wg_commit();
                    if (kb > 0) {
                        wg_wait<1>();
                        if (lane == 0) mbar_arrive(s_bar + 32 + ((stage + G_STAGES - 1) % G_STAGES) * 8);
                    }
                    if (++stage == G_STAGES) { stage = 0; phase ^= 1; }
                }
                wg_wait<0>();
                fence_regs(acc);
                if (lane == 0) mbar_arrive(s_bar + 32 + ((stage + G_STAGES - 1) % G_STAGES) * 8);
                const int row0 = mblk * 128 + wg * 64;
                if (wq == 0 && lane == 0) bulk_wait_read<0>();
                named_bar_sync(1 + wg, 128);
#pragma unroll
                for (int s = 0; s < 2; s++) {
                    const float* v16 = &acc[s * 16];
                    slot_norm(v16, SLOT_KB + s, (row0 >> 4) + wq, lane);
                    stmatrix_x4(epi + s * 4096 + st_off0, pack_bf16(v16[0], v16[1]), pack_bf16(v16[4], v16[5]),
                                pack_bf16(v16[8], v16[9]), pack_bf16(v16[12], v16[13]));
                    stmatrix_x4(epi + s * 4096 + st_off1, pack_bf16(v16[2], v16[3]), pack_bf16(v16[6], v16[7]),
                                pack_bf16(v16[10], v16[11]), pack_bf16(v16[14], v16[15]));
                }
                fence_proxy_async();
                named_bar_sync(1 + wg, 128);
                if (wq == 0 && lane == 0) {
                    tma_store_3d(&P.qkv_st, epi, 0, row0, SLOT_KB);
                    bulk_commit();
                }
            }
        }
        if (wq == 0 && lane == 0) bulk_wait<0>();
    }
}

__global__ void __launch_bounds__(G_THREADS, 1) out_kernel(const __grid_constant__ OutParams P) {
    extern __shared__ uint8_t smem_raw[];
    const uint32_t sbase = (smem_u32(smem_raw) + 1023u) & ~1023u;
    const uint32_t s_bar = sbase + G_STAGES * G_STAGE_BYTES + G_EPI_BYTES;
    const int tid = threadIdx.x, warp = tid >> 5, lane = tid & 31;
    const int t = blockIdx.x;
    const int prob = t >> 6, mblk = (t & 63) >> 2, nblk = t & 3;

    if (tid == 0) {
        for (int s = 0; s < G_STAGES; s++) { mbar_init(s_bar + s * 8, 1); mbar_init(s_bar + 32 + s * 8, 8); }
        fence_barrier_init();
    }
    __syncthreads();

    if (warp >= 8) {
        reg_dealloc<40>();
        if (warp == 8 && lane == 0) {
            pdl_wait();
            int stage = 0; uint32_t phase = 1;
            const CUtensorMap* mb = prob ? &P.wob : &P.woa;
            for (int kb = 0; kb < 16; kb++) {
                mbar_wait(s_bar + 32 + stage * 8, phase);
                const uint32_t full = s_bar + stage * 8;
                mbar_expect_tx(full, G_STAGE_BYTES);
                const uint32_t sa = sbase + stage * G_STAGE_BYTES;
                tma_load_2d(sa, &P.o, full, kb * 64, prob * SEQ + mblk * 128);
                tma_load_3d(sa + G_A_BYTES, mb, full, 0, kb * 64, nblk * 4);
                if (++stage == G_STAGES) { stage = 0; phase ^= 1; }
            }
        }
    } else {
        reg_alloc<232>();
        const int wg = warp >> 2, wq = warp & 3;
        int stage = 0; uint32_t phase = 0;
        float acc[128];
#pragma unroll
        for (int i = 0; i < 128; i++) acc[i] = 0.f;
        for (int kb = 0; kb < 16; kb++) {
            mbar_wait(s_bar + stage * 8, phase);
            const uint32_t sa = sbase + stage * G_STAGE_BYTES;
            const uint64_t da = make_desc(sa + wg * 8192, 16, 1024, 1);
            const uint64_t db = make_desc(sa + G_A_BYTES, 8192, 1024, 1);
            wg_fence();
#pragma unroll
            for (int kk = 0; kk < 4; kk++) wgmma_ss_n256_tb(acc, da + kk * 2, db + kk * 128);
            wg_commit();
            if (kb > 0) {
                wg_wait<1>();
                if (lane == 0) mbar_arrive(s_bar + 32 + ((stage + G_STAGES - 1) % G_STAGES) * 8);
            }
            if (++stage == G_STAGES) { stage = 0; phase ^= 1; }
        }
        wg_wait<0>();
        fence_regs(acc);
        named_bar_sync(1, 256);
        const uint32_t epi = sbase + wg * 32768;
        const int srow = wq * 16 + (lane & 7);
#pragma unroll
        for (int c = 0; c < 4; c++) {
#pragma unroll
            for (int h = 0; h < 2; h++) {
                const float* v16 = &acc[(c * 8 + h * 4) * 4];
                const uint32_t ch = (uint32_t)(h * 4 + (lane >> 3));
                const uint32_t a0 = epi + c * 8192 + srow * 128 + ((ch ^ (srow & 7)) << 4);
                const uint32_t a1 = a0 + 8 * 128;
                stmatrix_x4(a0, pack_bf16(v16[0], v16[1]), pack_bf16(v16[4], v16[5]),
                            pack_bf16(v16[8], v16[9]), pack_bf16(v16[12], v16[13]));
                stmatrix_x4(a1, pack_bf16(v16[2], v16[3]), pack_bf16(v16[6], v16[7]),
                            pack_bf16(v16[10], v16[11]), pack_bf16(v16[14], v16[15]));
            }
        }
        fence_proxy_async();
        named_bar_sync(2 + wg, 128);
        if (wq == 0 && lane == 0) {
            const int row0 = mblk * 128 + wg * 64;
            const int col0 = prob * DM + nblk * 256;
#pragma unroll
            for (int c = 0; c < 4; c++) tma_store_2d(&P.out_st, epi + c * 8192, col0 + c * 64, row0);
            bulk_commit();
            bulk_wait<0>();
        }
    }
}

constexpr int A_STAGES = 8;
constexpr int A_STAGE_BYTES = 16384;
constexpr int A_Q_BYTES = 16384;
constexpr int A_OFF_Q = A_STAGES * A_STAGE_BYTES;
constexpr int A_OFF_O = A_OFF_Q + 2 * A_Q_BYTES;
constexpr int A_OFF_ONES = A_OFF_O + 16384;
constexpr int A_OFF_BAR = A_OFF_ONES + 1024;
constexpr int A_SMEM = 1024 + A_OFF_BAR + 256;
constexpr int A_THREADS = 512;
constexpr int A_LOOKAHEAD = A_STAGES - 2;
constexpr int A_TILES = 512;
constexpr float FAST_BOUND2 = 48.0f * 48.0f;

#define EMU_MASK 0x5454

struct AttnParams {
    CUtensorMap qkv_ld, o_st;
};

template <int I> __device__ __forceinline__ float ex2_sel(float x) {
    if ((EMU_MASK >> (I & 15)) & 1) return ex2_poly(x); else return ex2_mufu(x);
}

template <int KK> __device__ __forceinline__ void softmax_fast_frag(const float (&s)[32], uint32_t (&p)[4]) {
    p[0] = pack_bf16(ex2_sel<KK * 8 + 0>(s[KK * 8 + 0]), ex2_sel<KK * 8 + 1>(s[KK * 8 + 1]));
    p[1] = pack_bf16(ex2_sel<KK * 8 + 2>(s[KK * 8 + 2]), ex2_sel<KK * 8 + 3>(s[KK * 8 + 3]));
    p[2] = pack_bf16(ex2_sel<KK * 8 + 4>(s[KK * 8 + 4]), ex2_sel<KK * 8 + 5>(s[KK * 8 + 5]));
    p[3] = pack_bf16(ex2_sel<KK * 8 + 6>(s[KK * 8 + 6]), ex2_sel<KK * 8 + 7>(s[KK * 8 + 7]));
}

__global__ void __launch_bounds__(A_THREADS, 1) attn_kernel(const __grid_constant__ AttnParams P) {
    extern __shared__ uint8_t smem_raw[];
    const uint32_t sbase = (smem_u32(smem_raw) + 1023u) & ~1023u;
    const uint32_t s_bar = sbase + A_OFF_BAR;
    const int tid = threadIdx.x, warp = tid >> 5, lane = tid & 31;

    if (tid == 0) {
        for (int s = 0; s < A_STAGES; s++) { mbar_init(s_bar + s * 8, 1); mbar_init(s_bar + 64 + s * 8, 16); }
        for (int s = 0; s < 2; s++) { mbar_init(s_bar + 128 + s * 8, 1); mbar_init(s_bar + 144 + s * 8, 16); }
        fence_barrier_init();
    }
    if (tid < 64) {
        uint8_t* gen = smem_raw + (sbase - smem_u32(smem_raw)) + A_OFF_ONES;
        *reinterpret_cast<uint4*>(gen + tid * 16) = make_uint4(0x00003F80u, 0u, 0u, 0u);
        fence_proxy_async();
    }
    __syncthreads();
    pdl_launch();
    pdl_wait();

    auto issue_load = [&](int L) {
        const int t = blockIdx.x + (L >> 4) * gridDim.x;
        if (t >= A_TILES) return;
        const int st = L & 15;
        const int prob = t >> 8, head = (t >> 3) & 31, rb = t & 7;
        if (st == 0) {
            const int it = L >> 4, qb = it & 1;
            mbar_wait(s_bar + 144 + qb * 8, ((it >> 1) & 1) ^ 1);
            mbar_expect_tx(s_bar + 128 + qb * 8, A_Q_BYTES);
            const int slotQ = (prob ? SLOT_QB : SLOT_QA) + head;
            tma_load_3d(sbase + A_OFF_Q + qb * A_Q_BYTES, &P.qkv_ld, s_bar + 128 + qb * 8, 0, rb * 256, slotQ);
            tma_load_3d(sbase + A_OFF_Q + qb * A_Q_BYTES + 8192, &P.qkv_ld, s_bar + 128 + qb * 8, 0, rb * 256 + 128, slotQ);
        }
        const int stg = L % A_STAGES;
        mbar_wait(s_bar + 64 + stg * 8, ((L / A_STAGES) & 1) ^ 1);
        const uint32_t full = s_bar + stg * 8;
        mbar_expect_tx(full, A_STAGE_BYTES);
        const uint32_t sa = sbase + stg * A_STAGE_BYTES;
        tma_load_3d(sa, &P.qkv_ld, full, 0, st * 128, prob ? SLOT_KB : SLOT_KA + head);
        tma_load_3d(sa + 8192, &P.qkv_ld, full, 0, st * 128, prob ? SLOT_VB : SLOT_VA + head);
    };
    if (tid == 0) {
        for (int L = 0; L < A_LOOKAHEAD; L++) issue_load(L);
    }
    __syncwarp();
    {
        const int wg = warp >> 2, wq = warp & 3;
        int stage = 0; uint32_t phase = 0;
        int it = 0;
        const uint32_t s_ones = sbase + A_OFF_ONES;
        const uint32_t s_ostage = sbase + A_OFF_O + warp * 1024;
        for (int t = blockIdx.x; t < A_TILES; t += gridDim.x, it++) {
            const int prob = t >> 8, head = (t >> 3) & 31, rb = t & 7;
            const int slotK = prob ? SLOT_KB : SLOT_KA + head;
            const int slotV = prob ? SLOT_VB : SLOT_VA + head;
            float kn2, vn2;
            {
                const float4 a = *reinterpret_cast<const float4*>(&g_n2[slotK * 128 + lane * 4]);
                const float4 b = *reinterpret_cast<const float4*>(&g_n2[slotV * 128 + lane * 4]);
                uint32_t ma = max(max(__float_as_uint(a.x), __float_as_uint(a.y)), max(__float_as_uint(a.z), __float_as_uint(a.w)));
                uint32_t mb = max(max(__float_as_uint(b.x), __float_as_uint(b.y)), max(__float_as_uint(b.z), __float_as_uint(b.w)));
                kn2 = __uint_as_float(__reduce_max_sync(0xffffffffu, ma));
                vn2 = __uint_as_float(__reduce_max_sync(0xffffffffu, mb));
            }
            const int qb = it & 1;
            mbar_wait(s_bar + 128 + qb * 8, (it >> 1) & 1);
            uint32_t q0[4], q1[4];
            {
                const int r = wg * 64 + wq * 16 + (lane & 7) + ((lane >> 3) & 1) * 8;
                const uint32_t base = sbase + A_OFF_Q + qb * A_Q_BYTES + r * 64;
                const uint32_t sw = (r >> 1) & 3;
                ldmatrix_x4(base + ((((lane >> 4)) ^ sw) << 4), q0);
                ldmatrix_x4(base + (((2 + (lane >> 4)) ^ sw) << 4), q1);
            }
            __syncwarp();
            if (lane == 0) mbar_arrive(s_bar + 144 + qb * 8);
            bool fast;
            {
                float a = 0.f, b = 0.f;
#pragma unroll
                for (int i = 0; i < 4; i++) {
                    const uint32_t u0 = q0[i], u1 = q1[i];
                    const float x0 = __uint_as_float(u0 << 16), x1 = __uint_as_float(u0 & 0xffff0000u);
                    const float y0 = __uint_as_float(u1 << 16), y1 = __uint_as_float(u1 & 0xffff0000u);
                    const float ss = x0 * x0 + x1 * x1 + y0 * y0 + y1 * y1;
                    if (i & 1) b += ss; else a += ss;
                }
                a += __shfl_xor_sync(0xffffffffu, a, 1); b += __shfl_xor_sync(0xffffffffu, b, 1);
                a += __shfl_xor_sync(0xffffffffu, a, 2); b += __shfl_xor_sync(0xffffffffu, b, 2);
                const bool ok = (a * kn2 <= FAST_BOUND2) && (b * kn2 <= FAST_BOUND2) && (vn2 <= 1e24f) && (vn2 >= 1e-24f);
                uint32_t r;
                asm volatile("{\n.reg .pred p, q;\nsetp.ne.u32 p, %1, 0;\nbar.red.and.pred q, %2, 128, p;\nselp.u32 %0, 1, 0, q;\n}\n"
                             : "=r"(r) : "r"((uint32_t)ok), "r"(1 + wg) : "memory");
                fast = r != 0;
            }
            float o[20];
#pragma unroll
            for (int i = 0; i < 20; i++) o[i] = 0.f;

            if (fast) {
                for (int st = 0; st < 16; st++) {
                    if (warp == st && lane == 0) issue_load(it * 16 + st + A_LOOKAHEAD);
                    __syncwarp();
                    mbar_wait(s_bar + stage * 8, phase);
                    const uint32_t sk = sbase + stage * A_STAGE_BYTES;
#pragma unroll
                    for (int sub = 0; sub < 2; sub++) {
                        float s[32];
                        const uint64_t dk = make_desc(sk + sub * 4096, 16, 512, 2);
                        wg_fence();
                        wgmma_rs_n64_z(s, q0, dk);
                        wgmma_rs_n64(s, q1, dk + 2);
                        wg_commit();
                        wg_wait<0>();
                        fence_regs(s);
                        fence_regs(o);
                        if (sub == 0 && st > 0) {
                            if (lane == 0) mbar_arrive(s_bar + 64 + ((stage + A_STAGES - 1) % A_STAGES) * 8);
                        }
                        uint32_t p0[4], p1[4], p2[4], p3[4];
                        softmax_fast_frag<0>(s, p0);
                        softmax_fast_frag<1>(s, p1);
                        softmax_fast_frag<2>(s, p2);
                        softmax_fast_frag<3>(s, p3);
                        const uint32_t sv = sk + 8192 + sub * 4096;
                        wg_fence();
                        wgmma_rs_n40_tb(o, p0, make_desc(sv, s_ones - sv, 512, 2));
                        wgmma_rs_n40_tb(o, p1, make_desc(sv + 1024, s_ones - sv - 1024, 512, 2));
                        wgmma_rs_n40_tb(o, p2, make_desc(sv + 2048, s_ones - sv - 2048, 512, 2));
                        wgmma_rs_n40_tb(o, p3, make_desc(sv + 3072, s_ones - sv - 3072, 512, 2));
                        wg_commit();
                    }
                    if (++stage == A_STAGES) { stage = 0; phase ^= 1; }
                }
            } else {
                float m0 = -INFINITY, m1 = -INFINITY;
                for (int st = 0; st < 16; st++) {
                    if (warp == st && lane == 0) issue_load(it * 16 + st + A_LOOKAHEAD);
                    __syncwarp();
                    mbar_wait(s_bar + stage * 8, phase);
                    const uint32_t sk = sbase + stage * A_STAGE_BYTES;
#pragma unroll 1
                    for (int sub = 0; sub < 2; sub++) {
                        float s[32];
                        const uint64_t dk = make_desc(sk + sub * 4096, 16, 512, 2);
                        wg_fence();
                        wgmma_rs_n64_z(s, q0, dk);
                        wgmma_rs_n64(s, q1, dk + 2);
                        wg_commit();
                        wg_wait<0>();
                        fence_regs(s);
                        fence_regs(o);
                        if (sub == 0 && st > 0) {
                            if (lane == 0) mbar_arrive(s_bar + 64 + ((stage + A_STAGES - 1) % A_STAGES) * 8);
                        }
                        float t0 = m0, t1 = m1;
#pragma unroll
                        for (int j = 0; j < 8; j++) {
                            t0 = fmaxf(t0, fmaxf(s[4 * j], s[4 * j + 1]));
                            t1 = fmaxf(t1, fmaxf(s[4 * j + 2], s[4 * j + 3]));
                        }
                        t0 = fmaxf(t0, __shfl_xor_sync(0xffffffffu, t0, 1)); t1 = fmaxf(t1, __shfl_xor_sync(0xffffffffu, t1, 1));
                        t0 = fmaxf(t0, __shfl_xor_sync(0xffffffffu, t0, 2)); t1 = fmaxf(t1, __shfl_xor_sync(0xffffffffu, t1, 2));
                        const float al0 = ex2_mufu(m0 - t0), al1 = ex2_mufu(m1 - t1);
                        m0 = t0; m1 = t1;
#pragma unroll
                        for (int j = 0; j < 5; j++) { o[4 * j] *= al0; o[4 * j + 1] *= al0; o[4 * j + 2] *= al1; o[4 * j + 3] *= al1; }
                        uint32_t p[4][4];
#pragma unroll
                        for (int kk = 0; kk < 4; kk++) {
                            p[kk][0] = pack_bf16(ex2_mufu(s[kk * 8 + 0] - m0), ex2_mufu(s[kk * 8 + 1] - m0));
                            p[kk][1] = pack_bf16(ex2_mufu(s[kk * 8 + 2] - m1), ex2_mufu(s[kk * 8 + 3] - m1));
                            p[kk][2] = pack_bf16(ex2_mufu(s[kk * 8 + 4] - m0), ex2_mufu(s[kk * 8 + 5] - m0));
                            p[kk][3] = pack_bf16(ex2_mufu(s[kk * 8 + 6] - m1), ex2_mufu(s[kk * 8 + 7] - m1));
                        }
                        const uint32_t sv = sk + 8192 + sub * 4096;
                        wg_fence();
#pragma unroll
                        for (int kk = 0; kk < 4; kk++)
                            wgmma_rs_n40_tb(o, p[kk], make_desc(sv + kk * 1024, s_ones - sv - kk * 1024, 512, 2));
                        wg_commit();
                    }
                    if (++stage == A_STAGES) { stage = 0; phase ^= 1; }
                }
            }
            wg_wait<0>();
            fence_regs(o);
            if (lane == 0) mbar_arrive(s_bar + 64 + ((stage + A_STAGES - 1) % A_STAGES) * 8);
            {
                const float l0 = __shfl_sync(0xffffffffu, o[16], lane & ~3);
                const float l1 = __shfl_sync(0xffffffffu, o[18], lane & ~3);
                const float r0 = 1.0f / l0, r1 = 1.0f / l1;
                if (lane == 0) bulk_wait_read<0>();
                __syncwarp();
                const int r = lane & 7;
                const uint32_t a0 = s_ostage + r * 64 + (((lane >> 3) ^ ((r >> 1) & 3)) << 4);
                stmatrix_x4(a0, pack_bf16(o[0] * r0, o[1] * r0), pack_bf16(o[4] * r0, o[5] * r0),
                            pack_bf16(o[8] * r0, o[9] * r0), pack_bf16(o[12] * r0, o[13] * r0));
                stmatrix_x4(a0 + 512, pack_bf16(o[2] * r1, o[3] * r1), pack_bf16(o[6] * r1, o[7] * r1),
                            pack_bf16(o[10] * r1, o[11] * r1), pack_bf16(o[14] * r1, o[15] * r1));
                fence_proxy_async();
                __syncwarp();
                if (lane == 0) {
                    tma_store_2d(&P.o_st, s_ostage, head * 32, prob * SEQ + rb * 256 + wg * 64 + wq * 16);
                    bulk_commit();
                }
            }
        }
        if (lane == 0) bulk_wait<0>();
    }
}

typedef CUresult (*EncodeFn)(CUtensorMap*, CUtensorMapDataType, cuuint32_t, void*, const cuuint64_t*, const cuuint64_t*,
                             const cuuint32_t*, const cuuint32_t*, CUtensorMapInterleave, CUtensorMapSwizzle,
                             CUtensorMapL2promotion, CUtensorMapFloatOOBfill);

void make_map(EncodeFn enc, CUtensorMap* m, const void* ptr, int rank, const uint64_t* dims, const uint64_t* strides_bytes,
              const uint32_t* box, CUtensorMapSwizzle swz) {
    cuuint64_t gd[3], gs[2];
    cuuint32_t bx[3], es[3] = {1, 1, 1};
    for (int i = 0; i < rank; i++) { gd[i] = dims[i]; bx[i] = box[i]; }
    for (int i = 0; i < rank - 1; i++) gs[i] = strides_bytes[i];
    enc(m, CU_TENSOR_MAP_DATA_TYPE_BFLOAT16, rank, const_cast<void*>(ptr), gd, gs, bx, es, CU_TENSOR_MAP_INTERLEAVE_NONE, swz,
        CU_TENSOR_MAP_L2_PROMOTION_L2_256B, CU_TENSOR_MAP_FLOAT_OOB_FILL_NONE);
}

void map_kmajor(EncodeFn enc, CUtensorMap* m, const void* p, uint64_t rows, uint64_t cols, uint32_t box_rows) {
    uint64_t d[2] = {cols, rows}, s[1] = {cols * 2};
    uint32_t b[2] = {64, box_rows};
    make_map(enc, m, p, 2, d, s, b, CU_TENSOR_MAP_SWIZZLE_128B);
}
void map_weight(EncodeFn enc, CUtensorMap* m, const void* p, uint64_t K, uint64_t N) {
    uint64_t d[3] = {64, K, N / 64}, s[2] = {N * 2, 128};
    uint32_t b[3] = {64, 64, 4};
    make_map(enc, m, p, 3, d, s, b, CU_TENSOR_MAP_SWIZZLE_128B);
}

template <typename Prm>
void launch(void (*kern)(const Prm), int grid, int threads, int smem, const Prm& prm, bool pdl) {
    cudaLaunchConfig_t cfg = {};
    cfg.gridDim = dim3(grid); cfg.blockDim = dim3(threads); cfg.dynamicSmemBytes = smem;
    cfg.stream = cudaStreamPerThread;
    cudaLaunchAttribute at[1];
    at[0].id = cudaLaunchAttributeProgrammaticStreamSerialization;
    at[0].val.programmaticStreamSerializationAllowed = 1;
    cfg.attrs = at; cfg.numAttrs = pdl ? 1 : 0;
    cudaLaunchKernelEx(&cfg, kern, prm);
}

}

extern "C" void kernel_launch(void* const* d_in, const int* in_sizes, int n_in, void* d_out, int out_size) {
    (void)in_sizes; (void)n_in; (void)out_size;
    static EncodeFn enc = nullptr;
    static void* p_qkv = nullptr;
    static void* p_o = nullptr;
    if (!enc) {
        void* fn = nullptr;
        cudaDriverEntryPointQueryResult qr;
        cudaGetDriverEntryPoint("cuTensorMapEncodeTiled", &fn, cudaEnableDefault, &qr);
        enc = (EncodeFn)fn;
        cudaGetSymbolAddress(&p_qkv, g_qkv);
        cudaGetSymbolAddress(&p_o, g_o);
        cudaFuncSetAttribute(proj_kernel, cudaFuncAttributeMaxDynamicSharedMemorySize, G_SMEM);
        cudaFuncSetAttribute(out_kernel, cudaFuncAttributeMaxDynamicSharedMemorySize, G_SMEM);
        cudaFuncSetAttribute(attn_kernel, cudaFuncAttributeMaxDynamicSharedMemorySize, A_SMEM);
    }
    const void* A_x = d_in[0]; const void* A_wqkv = d_in[1]; const void* A_wo = d_in[2];
    const void* B_x = d_in[3]; const void* B_wq = d_in[4]; const void* B_wk = d_in[5];
    const void* B_wv = d_in[6]; const void* B_wo = d_in[7];

    ProjParams pp;
    map_kmajor(enc, &pp.xa, A_x, SEQ, DM, 128);
    map_kmajor(enc, &pp.xb, B_x, SEQ, DM, 128);
    map_weight(enc, &pp.wqkv, A_wqkv, DM, 3 * DM);
    map_weight(enc, &pp.wq, B_wq, DM, DM);
    {
        uint64_t d[2] = {32, DM}, s[1] = {64};
        uint32_t b[2] = {32, 64};
        make_map(enc, &pp.wk, B_wk, 2, d, s, b, CU_TENSOR_MAP_SWIZZLE_64B);
        make_map(enc, &pp.wv, B_wv, 2, d, s, b, CU_TENSOR_MAP_SWIZZLE_64B);
    }
    {
        uint64_t d[3] = {32, SEQ, NSLOT}, s[2] = {64, (uint64_t)SEQ * 64};
        uint32_t b[3] = {32, 64, 4};
        make_map(enc, &pp.qkv_st, p_qkv, 3, d, s, b, CU_TENSOR_MAP_SWIZZLE_64B);
    }
    AttnParams ap;
    {
        uint64_t d[3] = {32, SEQ, NSLOT}, s[2] = {64, (uint64_t)SEQ * 64};
        uint32_t b[3] = {32, 128, 1};
        make_map(enc, &ap.qkv_ld, p_qkv, 3, d, s, b, CU_TENSOR_MAP_SWIZZLE_64B);
        uint64_t d2[2] = {DM, 2 * SEQ}, s2[1] = {DM * 2};
        uint32_t b2[2] = {32, 16};
        make_map(enc, &ap.o_st, p_o, 2, d2, s2, b2, CU_TENSOR_MAP_SWIZZLE_64B);
    }
    OutParams op;
    map_kmajor(enc, &op.o, p_o, 2 * SEQ, DM, 128);
    map_weight(enc, &op.woa, A_wo, DM, DM);
    map_weight(enc, &op.wob, B_wo, DM, DM);
    {
        uint64_t d[2] = {2 * DM, SEQ}, s[1] = {2 * DM * 2};
        uint32_t b[2] = {64, 64};
        make_map(enc, &op.out_st, d_out, 2, d, s, b, CU_TENSOR_MAP_SWIZZLE_128B);
    }
    launch(proj_kernel, 132, G_THREADS, G_SMEM, pp, false);
    launch(attn_kernel, 132, A_THREADS, A_SMEM, ap, true);
    launch(out_kernel, 128, G_THREADS, G_SMEM, op, true);
}
```

```cpp
#include <cuda_runtime.h>
#include <cuda_bf16.h>
#include <cuda_fp16.h>
#include <cuda.h>
#include <stdint.h>

namespace {

constexpr int SEQ = 2048;
constexpr int DM = 1024;
constexpr int NSLOT = 130;
constexpr int SLOT_QA = 0, SLOT_KA = 32, SLOT_KB = 64, SLOT_VA = 65, SLOT_VB = 97, SLOT_QB = 98;
constexpr int KV_STRIDE = SLOT_VA - SLOT_KA;
constexpr float QSCALE = 0.17677669529663687f * 1.4426950408889634f;

__device__ __align__(1024) __nv_bfloat16 g_qkv[NSLOT * SEQ * 32];
__device__ __align__(1024) __nv_bfloat16 g_o[2 * SEQ * DM];
#define TS(k, i)
#define TSX(k, i)
#define TST(t, k, i)
#define KS(i)
__device__ __align__(16) float g_n2[NSLOT * 128];

__device__ __forceinline__ uint32_t smem_u32(const void* p) { return (uint32_t)__cvta_generic_to_shared(p); }

__device__ __forceinline__ void mbar_init(uint32_t bar, uint32_t count) {
    asm volatile("mbarrier.init.shared::cta.b64 [%0], %1;" :: "r"(bar), "r"(count) : "memory");
}
__device__ __forceinline__ void mbar_expect_tx(uint32_t bar, uint32_t bytes) {
    asm volatile("mbarrier.arrive.expect_tx.shared::cta.b64 _, [%0], %1;" :: "r"(bar), "r"(bytes) : "memory");
}
__device__ __forceinline__ void mbar_arrive(uint32_t bar) {
    asm volatile("mbarrier.arrive.shared::cta.b64 _, [%0];" :: "r"(bar) : "memory");
}
__device__ __forceinline__ bool mbar_try(uint32_t bar, uint32_t parity) {
    uint32_t ok;
    asm volatile(
        "{\n"
        ".reg .pred p;\n"
        "mbarrier.try_wait.parity.shared::cta.b64 p, [%1], %2;\n"
        "selp.u32 %0, 1, 0, p;\n"
        "}\n" : "=r"(ok) : "r"(bar), "r"(parity) : "memory");
    return ok != 0;
}
__device__ __forceinline__ void mbar_wait(uint32_t bar, uint32_t parity) {
    if (mbar_try(bar, parity)) return;
    const uint32_t t0 = (uint32_t)clock();
    while (!mbar_try(bar, parity)) {
        if ((uint32_t)clock() - t0 > 0x0fffffffu) break;
    }
}
__device__ __forceinline__ void fence_barrier_init() { asm volatile("fence.mbarrier_init.release.cluster;" ::: "memory"); }
__device__ __forceinline__ void fence_proxy_async() { asm volatile("fence.proxy.async.shared::cta;" ::: "memory"); }

__device__ __forceinline__ void tma_load_2d(uint32_t dst, const CUtensorMap* map, uint32_t bar, int c0, int c1) {
    asm volatile("cp.async.bulk.tensor.2d.shared::cluster.global.mbarrier::complete_tx::bytes [%0], [%1, {%3, %4}], [%2];"
                 :: "r"(dst), "l"(map), "r"(bar), "r"(c0), "r"(c1) : "memory");
}
__device__ __forceinline__ void tma_load_3d(uint32_t dst, const CUtensorMap* map, uint32_t bar, int c0, int c1, int c2) {
    asm volatile("cp.async.bulk.tensor.3d.shared::cluster.global.mbarrier::complete_tx::bytes [%0], [%1, {%3, %4, %5}], [%2];"
                 :: "r"(dst), "l"(map), "r"(bar), "r"(c0), "r"(c1), "r"(c2) : "memory");
}
__device__ __forceinline__ void tma_load_4d(uint32_t dst, const CUtensorMap* map, uint32_t bar, int c0, int c1, int c2, int c3) {
    asm volatile("cp.async.bulk.tensor.4d.shared::cluster.global.mbarrier::complete_tx::bytes [%0], [%1, {%3, %4, %5, %6}], [%2];"
                 :: "r"(dst), "l"(map), "r"(bar), "r"(c0), "r"(c1), "r"(c2), "r"(c3) : "memory");
}
__device__ __forceinline__ void tma_load_3d_mc(uint32_t dst, const CUtensorMap* map, uint32_t bar, int c0, int c1, int c2, uint16_t mask) {
    asm volatile("cp.async.bulk.tensor.3d.shared::cluster.global.mbarrier::complete_tx::bytes.multicast::cluster [%0], [%1, {%3, %4, %5}], [%2], %6;"
                 :: "r"(dst), "l"(map), "r"(bar), "r"(c0), "r"(c1), "r"(c2), "h"(mask) : "memory");
}
__device__ __forceinline__ uint32_t cluster_rank() {
    uint32_t r;
    asm("mov.u32 %0, %%cluster_ctarank;" : "=r"(r));
    return r;
}
__device__ __forceinline__ uint32_t map_to_cta(uint32_t addr, uint32_t rank) {
    uint32_t r;
    asm("mapa.shared::cluster.u32 %0, %1, %2;" : "=r"(r) : "r"(addr), "r"(rank));
    return r;
}
__device__ __forceinline__ void mbar_arrive_cluster(uint32_t cluster_addr) {
    asm volatile("mbarrier.arrive.shared::cluster.b64 _, [%0];" :: "r"(cluster_addr) : "memory");
}
__device__ __forceinline__ void cluster_sync() {
    asm volatile("barrier.cluster.arrive.release.aligned;\nbarrier.cluster.wait.acquire.aligned;" ::: "memory");
}
__device__ __forceinline__ void tma_prefetch_2d(const CUtensorMap* map, int c0, int c1) {
    asm volatile("cp.async.bulk.prefetch.tensor.2d.L2.global.tile [%0, {%1, %2}];" :: "l"(map), "r"(c0), "r"(c1) : "memory");
}
__device__ __forceinline__ void tma_prefetch_3d(const CUtensorMap* map, int c0, int c1, int c2) {
    asm volatile("cp.async.bulk.prefetch.tensor.3d.L2.global.tile [%0, {%1, %2, %3}];" :: "l"(map), "r"(c0), "r"(c1), "r"(c2) : "memory");
}
__device__ __forceinline__ void tma_store_2d(const CUtensorMap* map, uint32_t src, int c0, int c1) {
    asm volatile("cp.async.bulk.tensor.2d.global.shared::cta.bulk_group [%0, {%2, %3}], [%1];"
                 :: "l"(map), "r"(src), "r"(c0), "r"(c1) : "memory");
}
__device__ __forceinline__ void tma_store_3d(const CUtensorMap* map, uint32_t src, int c0, int c1, int c2) {
    asm volatile("cp.async.bulk.tensor.3d.global.shared::cta.bulk_group [%0, {%2, %3, %4}], [%1];"
                 :: "l"(map), "r"(src), "r"(c0), "r"(c1), "r"(c2) : "memory");
}
__device__ __forceinline__ void bulk_store(void* dst, uint32_t src, uint32_t bytes) {
    asm volatile("cp.async.bulk.global.shared::cta.bulk_group [%0], [%1], %2;" :: "l"(dst), "r"(src), "r"(bytes) : "memory");
}
__device__ __forceinline__ void bulk_commit() { asm volatile("cp.async.bulk.commit_group;" ::: "memory"); }
template <int N> __device__ __forceinline__ void bulk_wait_read() { asm volatile("cp.async.bulk.wait_group.read %0;" :: "n"(N) : "memory"); }
template <int N> __device__ __forceinline__ void bulk_wait() { asm volatile("cp.async.bulk.wait_group %0;" :: "n"(N) : "memory"); }
#define END_WAIT() bulk_wait<0>()
__device__ __forceinline__ void prefetch_map(const CUtensorMap* map) {
    asm volatile("prefetch.tensormap [%0];" :: "l"(map) : "memory");
}
__device__ __forceinline__ void l2_prefetch(const void* p, uint32_t bytes) {
    asm volatile("cp.async.bulk.prefetch.L2.global [%0], %1;" :: "l"(p), "r"(bytes) : "memory");
}
__device__ __forceinline__ void pdl_wait() { asm volatile("griddepcontrol.wait;" ::: "memory"); }
__device__ __forceinline__ void pdl_launch() { asm volatile("griddepcontrol.launch_dependents;" ::: "memory"); }

__device__ __forceinline__ void wg_fence() { asm volatile("wgmma.fence.sync.aligned;" ::: "memory"); }
__device__ __forceinline__ void wg_commit() { asm volatile("wgmma.commit_group.sync.aligned;" ::: "memory"); }
template <int N> __device__ __forceinline__ void wg_wait() { asm volatile("wgmma.wait_group.sync.aligned %0;" :: "n"(N) : "memory"); }
template <int N> __device__ __forceinline__ void fence_regs(float (&r)[N]) {
#pragma unroll
    for (int i = 0; i < N; i++) asm volatile("" : "+f"(r[i]) :: "memory");
}

template <int N> __device__ __forceinline__ void reg_alloc() { asm volatile("setmaxnreg.inc.sync.aligned.u32 %0;" :: "n"(N)); }
template <int N> __device__ __forceinline__ void reg_dealloc() { asm volatile("setmaxnreg.dec.sync.aligned.u32 %0;" :: "n"(N)); }
__device__ __forceinline__ void named_bar_sync(int id, int n) { asm volatile("bar.sync %0, %1;" :: "r"(id), "r"(n) : "memory"); }

__device__ __forceinline__ uint32_t pack_bf16(float lo, float hi) {
    uint32_t r;
    asm("cvt.rn.bf16x2.f32 %0, %1, %2;" : "=r"(r) : "f"(hi), "f"(lo));
    return r;
}
__device__ __forceinline__ uint32_t pack_f16(float lo, float hi) {
    uint32_t r;
    asm("cvt.rn.f16x2.f32 %0, %1, %2;" : "=r"(r) : "f"(hi), "f"(lo));
    return r;
}
__device__ __forceinline__ void stmatrix_x4(uint32_t addr, uint32_t r0, uint32_t r1, uint32_t r2, uint32_t r3) {
    asm volatile("stmatrix.sync.aligned.m8n8.x4.shared.b16 [%0], {%1, %2, %3, %4};"
                 :: "r"(addr), "r"(r0), "r"(r1), "r"(r2), "r"(r3) : "memory");
}
__device__ __forceinline__ void ldmatrix_x4(uint32_t addr, uint32_t (&r)[4]) {
    asm volatile("ldmatrix.sync.aligned.m8n8.x4.shared.b16 {%0, %1, %2, %3}, [%4];"
                 : "=r"(r[0]), "=r"(r[1]), "=r"(r[2]), "=r"(r[3]) : "r"(addr) : "memory");
}
__device__ __forceinline__ float ex2_mufu(float x) {
    float y;
    asm("ex2.approx.ftz.f32 %0, %1;" : "=f"(y) : "f"(x));
    return y;
}
__device__ __forceinline__ uint64_t make_desc(uint32_t addr, uint32_t lbo, uint32_t sbo, uint32_t swz) {
    return (uint64_t)((addr & 0x3FFFF) >> 4) | ((uint64_t)((lbo >> 4) & 0x3FFF) << 16) |
           ((uint64_t)((sbo >> 4) & 0x3FFF) << 32) | ((uint64_t)swz << 62);
}

template <int OFF> __device__ __forceinline__ void wgmma_ss_n128_tb(float (&d)[128], uint64_t descA, uint64_t descB) {
    asm volatile(
        "wgmma.mma_async.sync.aligned.m64n128k16.f32.bf16.bf16 "
        "{%0, %1, %2, %3, %4, %5, %6, %7, %8, %9, %10, %11, %12, %13, %14, %15, "
        "%16, %17, %18, %19, %20, %21, %22, %23, %24, %25, %26, %27, %28, %29, %30, %31, "
        "%32, %33, %34, %35, %36, %37, %38, %39, %40, %41, %42, %43, %44, %45, %46, %47, "
        "%48, %49, %50, %51, %52, %53, %54, %55, %56, %57, %58, %59, %60, %61, %62, %63}, "
        "%64, %65, 1, 1, 1, 0, 1;\n"
        : "+f"(d[OFF + 0]), "+f"(d[OFF + 1]), "+f"(d[OFF + 2]), "+f"(d[OFF + 3]), "+f"(d[OFF + 4]), "+f"(d[OFF + 5]),
          "+f"(d[OFF + 6]), "+f"(d[OFF + 7]), "+f"(d[OFF + 8]), "+f"(d[OFF + 9]), "+f"(d[OFF + 10]), "+f"(d[OFF + 11]),
          "+f"(d[OFF + 12]), "+f"(d[OFF + 13]), "+f"(d[OFF + 14]), "+f"(d[OFF + 15]), "+f"(d[OFF + 16]), "+f"(d[OFF + 17]),
          "+f"(d[OFF + 18]), "+f"(d[OFF + 19]), "+f"(d[OFF + 20]), "+f"(d[OFF + 21]), "+f"(d[OFF + 22]), "+f"(d[OFF + 23]),
          "+f"(d[OFF + 24]), "+f"(d[OFF + 25]), "+f"(d[OFF + 26]), "+f"(d[OFF + 27]), "+f"(d[OFF + 28]), "+f"(d[OFF + 29]),
          "+f"(d[OFF + 30]), "+f"(d[OFF + 31]), "+f"(d[OFF + 32]), "+f"(d[OFF + 33]), "+f"(d[OFF + 34]), "+f"(d[OFF + 35]),
          "+f"(d[OFF + 36]), "+f"(d[OFF + 37]), "+f"(d[OFF + 38]), "+f"(d[OFF + 39]), "+f"(d[OFF + 40]), "+f"(d[OFF + 41]),
          "+f"(d[OFF + 42]), "+f"(d[OFF + 43]), "+f"(d[OFF + 44]), "+f"(d[OFF + 45]), "+f"(d[OFF + 46]), "+f"(d[OFF + 47]),
          "+f"(d[OFF + 48]), "+f"(d[OFF + 49]), "+f"(d[OFF + 50]), "+f"(d[OFF + 51]), "+f"(d[OFF + 52]), "+f"(d[OFF + 53]),
          "+f"(d[OFF + 54]), "+f"(d[OFF + 55]), "+f"(d[OFF + 56]), "+f"(d[OFF + 57]), "+f"(d[OFF + 58]), "+f"(d[OFF + 59]),
          "+f"(d[OFF + 60]), "+f"(d[OFF + 61]), "+f"(d[OFF + 62]), "+f"(d[OFF + 63])
        : "l"(descA), "l"(descB));
}
template <int OFF> __device__ __forceinline__ void wgmma_ss_n128_tb_z(float (&d)[128], uint64_t descA, uint64_t descB) {
    asm volatile(
        "wgmma.mma_async.sync.aligned.m64n128k16.f32.bf16.bf16 "
        "{%0, %1, %2, %3, %4, %5, %6, %7, %8, %9, %10, %11, %12, %13, %14, %15, "
        "%16, %17, %18, %19, %20, %21, %22, %23, %24, %25, %26, %27, %28, %29, %30, %31, "
        "%32, %33, %34, %35, %36, %37, %38, %39, %40, %41, %42, %43, %44, %45, %46, %47, "
        "%48, %49, %50, %51, %52, %53, %54, %55, %56, %57, %58, %59, %60, %61, %62, %63}, "
        "%64, %65, 0, 1, 1, 0, 1;\n"
        : "=f"(d[OFF + 0]), "=f"(d[OFF + 1]), "=f"(d[OFF + 2]), "=f"(d[OFF + 3]), "=f"(d[OFF + 4]), "=f"(d[OFF + 5]),
          "=f"(d[OFF + 6]), "=f"(d[OFF + 7]), "=f"(d[OFF + 8]), "=f"(d[OFF + 9]), "=f"(d[OFF + 10]), "=f"(d[OFF + 11]),
          "=f"(d[OFF + 12]), "=f"(d[OFF + 13]), "=f"(d[OFF + 14]), "=f"(d[OFF + 15]), "=f"(d[OFF + 16]), "=f"(d[OFF + 17]),
          "=f"(d[OFF + 18]), "=f"(d[OFF + 19]), "=f"(d[OFF + 20]), "=f"(d[OFF + 21]), "=f"(d[OFF + 22]), "=f"(d[OFF + 23]),
          "=f"(d[OFF + 24]), "=f"(d[OFF + 25]), "=f"(d[OFF + 26]), "=f"(d[OFF + 27]), "=f"(d[OFF + 28]), "=f"(d[OFF + 29]),
          "=f"(d[OFF + 30]), "=f"(d[OFF + 31]), "=f"(d[OFF + 32]), "=f"(d[OFF + 33]), "=f"(d[OFF + 34]), "=f"(d[OFF + 35]),
          "=f"(d[OFF + 36]), "=f"(d[OFF + 37]), "=f"(d[OFF + 38]), "=f"(d[OFF + 39]), "=f"(d[OFF + 40]), "=f"(d[OFF + 41]),
          "=f"(d[OFF + 42]), "=f"(d[OFF + 43]), "=f"(d[OFF + 44]), "=f"(d[OFF + 45]), "=f"(d[OFF + 46]), "=f"(d[OFF + 47]),
          "=f"(d[OFF + 48]), "=f"(d[OFF + 49]), "=f"(d[OFF + 50]), "=f"(d[OFF + 51]), "=f"(d[OFF + 52]), "=f"(d[OFF + 53]),
          "=f"(d[OFF + 54]), "=f"(d[OFF + 55]), "=f"(d[OFF + 56]), "=f"(d[OFF + 57]), "=f"(d[OFF + 58]), "=f"(d[OFF + 59]),
          "=f"(d[OFF + 60]), "=f"(d[OFF + 61]), "=f"(d[OFF + 62]), "=f"(d[OFF + 63])
        : "l"(descA), "l"(descB));
}
__device__ __forceinline__ void wgmma_ss_n64_tb(float (&d)[32], uint64_t descA, uint64_t descB) {
    asm volatile(
        "wgmma.mma_async.sync.aligned.m64n64k16.f32.bf16.bf16 "
        "{%0, %1, %2, %3, %4, %5, %6, %7, %8, %9, %10, %11, %12, %13, %14, %15, "
        "%16, %17, %18, %19, %20, %21, %22, %23, %24, %25, %26, %27, %28, %29, %30, %31}, "
        "%32, %33, 1, 1, 1, 0, 1;\n"
        : "+f"(d[0]), "+f"(d[1]), "+f"(d[2]), "+f"(d[3]), "+f"(d[4]), "+f"(d[5]), "+f"(d[6]), "+f"(d[7]),
          "+f"(d[8]), "+f"(d[9]), "+f"(d[10]), "+f"(d[11]), "+f"(d[12]), "+f"(d[13]), "+f"(d[14]), "+f"(d[15]),
          "+f"(d[16]), "+f"(d[17]), "+f"(d[18]), "+f"(d[19]), "+f"(d[20]), "+f"(d[21]), "+f"(d[22]), "+f"(d[23]),
          "+f"(d[24]), "+f"(d[25]), "+f"(d[26]), "+f"(d[27]), "+f"(d[28]), "+f"(d[29]), "+f"(d[30]), "+f"(d[31])
        : "l"(descA), "l"(descB));
}
__device__ __forceinline__ void wgmma_rs_n64(float (&d)[32], const uint32_t (&a)[4], uint64_t descB) {
    asm volatile(
        "wgmma.mma_async.sync.aligned.m64n64k16.f32.bf16.bf16 "
        "{%0, %1, %2, %3, %4, %5, %6, %7, %8, %9, %10, %11, %12, %13, %14, %15, "
        "%16, %17, %18, %19, %20, %21, %22, %23, %24, %25, %26, %27, %28, %29, %30, %31}, "
        "{%32, %33, %34, %35}, %36, 1, 1, 1, 0;\n"
        : "+f"(d[0]), "+f"(d[1]), "+f"(d[2]), "+f"(d[3]), "+f"(d[4]), "+f"(d[5]), "+f"(d[6]), "+f"(d[7]),
          "+f"(d[8]), "+f"(d[9]), "+f"(d[10]), "+f"(d[11]), "+f"(d[12]), "+f"(d[13]), "+f"(d[14]), "+f"(d[15]),
          "+f"(d[16]), "+f"(d[17]), "+f"(d[18]), "+f"(d[19]), "+f"(d[20]), "+f"(d[21]), "+f"(d[22]), "+f"(d[23]),
          "+f"(d[24]), "+f"(d[25]), "+f"(d[26]), "+f"(d[27]), "+f"(d[28]), "+f"(d[29]), "+f"(d[30]), "+f"(d[31])
        : "r"(a[0]), "r"(a[1]), "r"(a[2]), "r"(a[3]), "l"(descB));
}
__device__ __forceinline__ void wgmma_rs_n64_z(float (&d)[32], const uint32_t (&a)[4], uint64_t descB) {
    asm volatile(
        "wgmma.mma_async.sync.aligned.m64n64k16.f32.bf16.bf16 "
        "{%0, %1, %2, %3, %4, %5, %6, %7, %8, %9, %10, %11, %12, %13, %14, %15, "
        "%16, %17, %18, %19, %20, %21, %22, %23, %24, %25, %26, %27, %28, %29, %30, %31}, "
        "{%32, %33, %34, %35}, %36, 0, 1, 1, 0;\n"
        : "=f"(d[0]), "=f"(d[1]), "=f"(d[2]), "=f"(d[3]), "=f"(d[4]), "=f"(d[5]), "=f"(d[6]), "=f"(d[7]),
          "=f"(d[8]), "=f"(d[9]), "=f"(d[10]), "=f"(d[11]), "=f"(d[12]), "=f"(d[13]), "=f"(d[14]), "=f"(d[15]),
          "=f"(d[16]), "=f"(d[17]), "=f"(d[18]), "=f"(d[19]), "=f"(d[20]), "=f"(d[21]), "=f"(d[22]), "=f"(d[23]),
          "=f"(d[24]), "=f"(d[25]), "=f"(d[26]), "=f"(d[27]), "=f"(d[28]), "=f"(d[29]), "=f"(d[30]), "=f"(d[31])
        : "r"(a[0]), "r"(a[1]), "r"(a[2]), "r"(a[3]), "l"(descB));
}
__device__ __forceinline__ void wgmma_rs_n40_tb(float (&d)[20], const uint32_t (&a)[4], uint64_t descB) {
    asm volatile(
        "wgmma.mma_async.sync.aligned.m64n40k16.f32.bf16.bf16 "
        "{%0, %1, %2, %3, %4, %5, %6, %7, %8, %9, %10, %11, %12, %13, %14, %15, "
        "%16, %17, %18, %19}, "
        "{%20, %21, %22, %23}, %24, 1, 1, 1, 1;\n"
        : "+f"(d[0]), "+f"(d[1]), "+f"(d[2]), "+f"(d[3]), "+f"(d[4]), "+f"(d[5]), "+f"(d[6]), "+f"(d[7]),
          "+f"(d[8]), "+f"(d[9]), "+f"(d[10]), "+f"(d[11]), "+f"(d[12]), "+f"(d[13]), "+f"(d[14]), "+f"(d[15]),
          "+f"(d[16]), "+f"(d[17]), "+f"(d[18]), "+f"(d[19])
        : "r"(a[0]), "r"(a[1]), "r"(a[2]), "r"(a[3]), "l"(descB));
}
__device__ __forceinline__ void wgmma_rs_n64_h(uint32_t (&d)[16], const uint32_t (&a)[4], uint64_t descB) {
    asm volatile(
        "wgmma.mma_async.sync.aligned.m64n64k16.f16.f16.f16 "
        "{%0, %1, %2, %3, %4, %5, %6, %7, %8, %9, %10, %11, %12, %13, %14, %15}, "
        "{%16, %17, %18, %19}, %20, 1, 1, 1, 0;\n"
        : "+r"(d[0]), "+r"(d[1]), "+r"(d[2]), "+r"(d[3]), "+r"(d[4]), "+r"(d[5]), "+r"(d[6]), "+r"(d[7]),
          "+r"(d[8]), "+r"(d[9]), "+r"(d[10]), "+r"(d[11]), "+r"(d[12]), "+r"(d[13]), "+r"(d[14]), "+r"(d[15])
        : "r"(a[0]), "r"(a[1]), "r"(a[2]), "r"(a[3]), "l"(descB));
}
__device__ __forceinline__ void wgmma_rs_n64_h_z(uint32_t (&d)[16], const uint32_t (&a)[4], uint64_t descB) {
    asm volatile(
        "wgmma.mma_async.sync.aligned.m64n64k16.f16.f16.f16 "
        "{%0, %1, %2, %3, %4, %5, %6, %7, %8, %9, %10, %11, %12, %13, %14, %15}, "
        "{%16, %17, %18, %19}, %20, 0, 1, 1, 0;\n"
        : "=r"(d[0]), "=r"(d[1]), "=r"(d[2]), "=r"(d[3]), "=r"(d[4]), "=r"(d[5]), "=r"(d[6]), "=r"(d[7]),
          "=r"(d[8]), "=r"(d[9]), "=r"(d[10]), "=r"(d[11]), "=r"(d[12]), "=r"(d[13]), "=r"(d[14]), "=r"(d[15])
        : "r"(a[0]), "r"(a[1]), "r"(a[2]), "r"(a[3]), "l"(descB));
}
__device__ __forceinline__ void wgmma_rs_n40_tb_h(uint32_t (&d)[10], const uint32_t (&a)[4], uint64_t descB) {
    asm volatile(
        "wgmma.mma_async.sync.aligned.m64n40k16.f16.f16.f16 "
        "{%0, %1, %2, %3, %4, %5, %6, %7, %8, %9}, "
        "{%10, %11, %12, %13}, %14, 1, 1, 1, 1;\n"
        : "+r"(d[0]), "+r"(d[1]), "+r"(d[2]), "+r"(d[3]), "+r"(d[4]), "+r"(d[5]), "+r"(d[6]), "+r"(d[7]),
          "+r"(d[8]), "+r"(d[9])
        : "r"(a[0]), "r"(a[1]), "r"(a[2]), "r"(a[3]), "l"(descB));
}

constexpr int G_STAGES = 4;
constexpr int G_A_BYTES = 128 * 64 * 2;
constexpr int G_B_BYTES = 64 * 256 * 2;
constexpr int G_STAGE_BYTES = G_A_BYTES + G_B_BYTES;
constexpr int KV_STAGES = 8;
constexpr int KV_STAGE_BYTES = G_A_BYTES + 8192;
constexpr int OFF_EPI = G_STAGES * G_STAGE_BYTES;
constexpr int OFF_ONES = OFF_EPI + 32768;
constexpr int OFF_BAR = OFF_ONES + 1024;
constexpr int SMEM_BYTES = OFF_BAR + 1024;
constexpr uint32_t SMEM_BASE = 0x400;
constexpr int B_GFULL = 0, B_GEMPTY = 32, B_KVFULL = 64, B_KVEMPTY = 128;
constexpr int B_AFULL = 192, B_AEMPTY = 224, B_QFULL = 256, B_QEMPTY = 272, B_REDO = 288;
constexpr int B_OFULL = 296, B_OEMPTY = 328, B_EPI = 360, B_EPOCH = 376;
constexpr int S_REDO = 384;
constexpr int S_KB = 392;
constexpr int S_EPOCH = 396;
constexpr int S_INFO = 400;
constexpr int S_PF = 432;
constexpr int S_OCNT = 448;
constexpr int S_KS = 512;
constexpr int NTHREADS = 512;
constexpr int NCTA = 132;

struct Params {
    CUtensorMap xa, xb, wqkv, wq, wk, wv, qkv_st, qkv_st1, o_st, o, woa, wob, out_st;
    uint64_t dtab[96];
    const uint8_t *p_xa, *p_xb, *p_wqkv, *p_wq, *p_woa, *p_wob;
};

constexpr int C_QB = 0, C_KVB = 32, C_A = 64, C_RDYB = 96, C_RDYA = 128;
constexpr int C_O = 160;
constexpr uint32_t N_QB = 64 * 8, N_KVB = 32, N_A = 192 * 8, N_RDYB = 1, N_RDYA = 16, N_O = 2 * 8 * 16;
__device__ unsigned long long g_launch;
__device__ __align__(128) uint32_t g_cnt[7 * 32];
__device__ __align__(16) float4 g_stat[33];

__device__ __forceinline__ void signal(int c) {
    asm volatile("red.release.gpu.global.add.u32 [%0], 1;" :: "l"(&g_cnt[c]) : "memory");
}
__device__ __forceinline__ uint32_t ld_acquire(int c) {
    uint32_t v;
    asm volatile("ld.acquire.gpu.global.u32 %0, [%1];" : "=r"(v) : "l"(&g_cnt[c]) : "memory");
    return v;
}
__device__ __forceinline__ void await(int c, uint32_t per_launch, uint32_t epoch) {
    const uint32_t target = (epoch + 1) * per_launch;
    if ((int)(ld_acquire(c) - target) >= 0) return;
    const uint32_t t0 = (uint32_t)clock();
    while ((int)(ld_acquire(c) - target) < 0) {
        __nanosleep(64);
        if ((uint32_t)clock() - t0 > 0x0fffffffu) break;
    }
}
__device__ __forceinline__ void fence_proxy_all() { asm volatile("fence.proxy.async;" ::: "memory"); }
__device__ __forceinline__ uint32_t get_epoch(uint32_t s_bar) {
    mbar_wait(s_bar + B_EPOCH, 0);
    uint32_t e;
    asm volatile("ld.volatile.shared.u32 %0, [%1];" : "=r"(e) : "r"(s_bar + S_EPOCH) : "memory");
    return e;
}
__device__ __forceinline__ void bulk_load(uint32_t dst, const void* src, uint32_t bytes, uint32_t bar) {
    asm volatile("cp.async.bulk.shared::cluster.global.mbarrier::complete_tx::bytes [%0], [%1], %2, [%3];"
                 :: "r"(dst), "l"(src), "r"(bytes), "r"(bar) : "memory");
}

__device__ __forceinline__ bool kv_is_f16(uint32_t n2, bool is_v) {
    if (is_v) return n2 == 0u || (n2 >= 0x36800000u   && n2 <= 0x4D800000u  );
    return n2 <= 0x4B800000u;
}

template <int NS>
__device__ __forceinline__ void slot_norms(const float* v, uint32_t (&n2)[NS], int slot, int slot_step, int grp16, int lane) {
    float a[NS], b[NS];
#pragma unroll
    for (int s = 0; s < NS; s++) {
        a[s] = v[16 * s] * v[16 * s]; b[s] = v[16 * s + 2] * v[16 * s + 2];
        a[s] = fmaf(v[16 * s + 1], v[16 * s + 1], a[s]); b[s] = fmaf(v[16 * s + 3], v[16 * s + 3], b[s]);
#pragma unroll
        for (int j = 1; j < 4; j++) {
            a[s] = fmaf(v[16 * s + 4 * j + 0], v[16 * s + 4 * j + 0], a[s]);
            b[s] = fmaf(v[16 * s + 4 * j + 2], v[16 * s + 4 * j + 2], b[s]);
            a[s] = fmaf(v[16 * s + 4 * j + 1], v[16 * s + 4 * j + 1], a[s]);
            b[s] = fmaf(v[16 * s + 4 * j + 3], v[16 * s + 4 * j + 3], b[s]);
        }
    }
#pragma unroll
    for (int x = 1; x <= 2; x++) {
#pragma unroll
        for (int s = 0; s < NS; s++) {
            a[s] += __shfl_xor_sync(0xffffffffu, a[s], x);
            b[s] += __shfl_xor_sync(0xffffffffu, b[s], x);
        }
    }
#pragma unroll
    for (int s = 0; s < NS; s++)
        n2[s] = __reduce_max_sync(0xffffffffu, max(__float_as_uint(a[s]) & 0x7fffffffu, __float_as_uint(b[s]) & 0x7fffffffu));
    if (lane == 0) {
#pragma unroll
        for (int s = 0; s < NS; s++) g_n2[(slot + s * slot_step) * 128 + grp16] = __uint_as_float(n2[s]);
    }
}
template <bool F16> __device__ __forceinline__ uint32_t pack2(float lo, float hi) { return F16 ? pack_f16(lo, hi) : pack_bf16(lo, hi); }
template <bool F16> __device__ __forceinline__ void pack_slot(uint32_t* p, const float* v, float sc) {
#pragma unroll
    for (int j = 0; j < 4; j++) {
        p[j] = pack2<F16>(v[4 * j] * sc, v[4 * j + 1] * sc);
        p[4 + j] = pack2<F16>(v[4 * j + 2] * sc, v[4 * j + 3] * sc);
    }
}
__device__ __forceinline__ void stage_slot(uint32_t a, const uint32_t* p) {
    stmatrix_x4(a, p[0], p[1], p[2], p[3]);
    stmatrix_x4(a + 512, p[4], p[5], p[6], p[7]);
}

#define MAPV 0
#define PRIO_KB 13
#define EV0 1
#define EVS 2
#define EVW 1
#define SIG_KB 10
#define PFT_U 0
#define PFT_N 4
#define TLB_XA 0
#define EARLY_LD 1
#define DEFER_LAST 1
#define ST_STEP 1
#define FLUSH_KB 2
#define PF2_DELAY 0
#define PF_WO 1
template <bool UNROLL, typename F>
__device__ __forceinline__ void gemm_tile(float (&acc)[128], uint32_t sbase, uint32_t full, uint32_t empty, int wg, int lane, bool release, F&& mid, int ks0 = 0) {
    const uint64_t da0 = make_desc(SMEM_BASE + wg * 8192, 16, 1024, 1);
    const uint64_t db0 = make_desc(SMEM_BASE + G_A_BYTES, 8192, 1024, 1);
    [[maybe_unused]] const uint32_t s_bar = sbase + OFF_BAR;
    auto step = [&](int kb, bool first) {
        const int stage = kb & 3;
        mbar_wait(full + stage * 8, (kb >> 2) & 1);
        if (kb == PRIO_KB && wg == 1) named_bar_sync(3, 256);
        KS(ks0 + kb * 2);
        const uint64_t da = da0 + stage * (G_STAGE_BYTES >> 4), db = db0 + stage * (G_STAGE_BYTES >> 4);
        wg_fence();
        if (first) { wgmma_ss_n128_tb_z<0>(acc, da, db); wgmma_ss_n128_tb_z<64>(acc, da, db + 1024); }
        else { wgmma_ss_n128_tb<0>(acc, da, db); wgmma_ss_n128_tb<64>(acc, da, db + 1024); }
#pragma unroll
        for (int kk = 1; kk < 4; kk++) {
            wgmma_ss_n128_tb<0>(acc, da + kk * 2, db + kk * 128);
            wgmma_ss_n128_tb<64>(acc, da + kk * 2, db + 1024 + kk * 128);
        }
        wg_commit();
        if (kb == 15 && wg == 0) asm volatile("bar.arrive 3, 256;" ::: "memory");
        KS(ks0 + kb * 2 + 1);
    };
    auto rel = [&](int kb) {
        if (kb > 0 && (release || kb <= 16 - G_STAGES)) {
            wg_wait<1>();
            if (lane == 0) mbar_arrive(empty + ((kb - 1) & 3) * 8);
        }
    };
#pragma unroll
    for (int kb = 0; kb < (UNROLL ? 16 : 4); kb++) {
        step(kb, kb == 0);
        mid(kb);
        rel(kb);
    }
    if (!UNROLL) {
#pragma unroll 1
        for (int kb = 4; kb < 16; kb++) {
            step(kb, false);
            rel(kb);
        }
    }
    wg_wait<0>();
    fence_regs(acc);
    if (release && lane == 0) mbar_arrive(empty + 3 * 8);
}

__device__ __forceinline__ void proj_tile(int cta, int it, bool& isA, int& mblk, int& nblk) {
    const bool lo = cta < 64;
    const bool is_q = lo == (it == 0);
    isA = !(lo && it == 0);
    if (is_q) { nblk = (cta >> 4) & 3; mblk = cta & 15; }
    else { nblk = 4 + ((cta >> 3) & 7); mblk = (cta & 7) + it * 8; }
}
__device__ __forceinline__ int out_tiles(int cta) { return cta < 100 ? 1 : (cta < 116 ? 0 : (cta < 128 ? 2 : 1)); }
__device__ __forceinline__ void out_tile(int cta, int i, int& prob, int& mblk, int& nblk) {
    prob = (cta >= 36 && cta < 100) ? 0 : 1;
    const int v = cta < 36 ? 28 + cta : (cta < 100 ? cta - 36 : (cta < 128 ? (cta - 116) * 2 + i : 24 + (cta - 128)));
    mblk = v >> 2; nblk = v & 3;
}

constexpr int A_KV_BYTES = 32768;
constexpr int A_V_OFF = 16384;
constexpr int NWG = 4;
constexpr int A_Q_BYTES = NWG * 4096;
constexpr int A_OFF_Q = OFF_EPI;
constexpr int A_TILES = 512;
constexpr float FAST_BOUND2 = 48.0f * 48.0f;

#define EMU_H 0x3733
#define SIG_STEP 5
#define RF_STEP 0

#define USE_LEA 1
__device__ __forceinline__ uint32_t hadd2(uint32_t a, uint32_t b) {
    uint32_t r;
    asm("add.rn.f16x2 %0, %1, %2;" : "=r"(r) : "r"(a), "r"(b));
    return r;
}
__device__ __forceinline__ uint32_t hmax2(uint32_t a, uint32_t b) {
    uint32_t r;
    asm("max.f16x2 %0, %1, %2;" : "=r"(r) : "r"(a), "r"(b));
    return r;
}
__device__ __forceinline__ uint32_t ex2_h_mufu(uint32_t x, uint32_t negc) {
    uint32_t y;
    asm("ex2.approx.f16x2 %0, %1;" : "=r"(y) : "r"(hadd2(x, negc)));
    return y;
}
__device__ __forceinline__ uint32_t ex2_h_emu(uint32_t x, uint32_t M, uint32_t kb) {
    uint32_t t, r, f, p, q;
    asm("add.rn.f16x2 %0, %1, %2;" : "=r"(t) : "r"(x), "r"(M));
    asm("sub.rn.f16x2 %0, %1, %2;" : "=r"(r) : "r"(t), "r"(M));
    asm("sub.rn.f16x2 %0, %1, %2;" : "=r"(f) : "r"(x), "r"(r));
    asm("fma.rn.f16x2 %0, %1, %2, %3;" : "=r"(p) : "r"(f), "r"(0x01590159u), "r"(0x03FB03FBu));
    asm("fma.rn.f16x2 %0, %1, %2, %3;" : "=r"(q) : "r"(p), "r"(f), "r"(0x05A905A9u));
    const uint32_t e = __viaddmin_s16x2_relu(t, kb, 0x001E001Eu);
    return q + __funnelshift_l(e, e, 10);
}
#define W0_FIX 0
template <int I> struct ExpPackH {
    static __device__ __forceinline__ void run(const uint32_t (&s)[16], uint32_t (&p)[4][4], const uint32_t (&nc)[2], const uint32_t (&M)[2], uint32_t kb) {
        if ((EMU_H >> I) & 1) p[I >> 2][I & 3] = ex2_h_emu(s[I], M[I & 1], kb); else p[I >> 2][I & 3] = ex2_h_mufu(s[I], nc[I & 1]);
        ExpPackH<I + 1>::run(s, p, nc, M, kb);
    }
};
template <> struct ExpPackH<16> {
    static __device__ __forceinline__ void run(const uint32_t (&)[16], uint32_t (&)[4][4], const uint32_t (&)[2], const uint32_t (&)[2], uint32_t) {}
};
template <int N> __device__ __forceinline__ void fence_regs_u(uint32_t (&r)[N]) {
#pragma unroll
    for (int i = 0; i < N; i++) asm volatile("" : "+r"(r[i]) :: "memory");
}
__device__ __forceinline__ float row_shift(float mx, float mean, float var) {
    float sd;
    asm("sqrt.approx.f32 %0, %1;" : "=f"(sd) : "f"(var));
    const float g = fmaxf(3.45f * sd - 6.0f, 0.35f * var - 1.5f);
    const float cm = ceilf(mx);
    const float c = fmaxf(cm - 6.0f, fminf(ceilf(mean + g), cm + 4.0f));
    return fminf(fmaxf(c, -128.0f), 128.0f);
}

__host__ __device__ constexpr uint32_t a_koff(int j) { return (j >> 2) * G_STAGE_BYTES + G_A_BYTES + (j & 3) * 4096; }
__host__ __device__ constexpr uint32_t a_voff(int j) { return a_koff(j) + A_V_OFF; }
__host__ __device__ constexpr uint64_t a_desc(uint32_t off, uint32_t lbo16) {
    return (uint64_t)(((SMEM_BASE + off) >> 4) | (lbo16 << 16)) | ((uint64_t)0x80000020u << 32);
}
__host__ __device__ constexpr uint64_t a_kdesc(int j, int half) { return a_desc(a_koff(j) + half * 32, 1); }
__host__ __device__ constexpr uint64_t a_vdesc(int j, int kk) {
    return a_desc(a_voff(j) + kk * 1024, (OFF_ONES - (a_voff(j) + kk * 1024)) >> 4);
}

__device__ __forceinline__ void issue_qk_h(uint32_t (&s)[16], const uint32_t (&q0)[4], const uint32_t (&q1)[4], uint64_t d0, uint64_t d1) {
    wgmma_rs_n64_h_z(s, q0, d0);
    wgmma_rs_n64_h(s, q1, d1);
}
__device__ __forceinline__ void issue_pv_h(uint32_t (&o)[10], const uint32_t (&p)[4][4], uint64_t d0, uint64_t d1, uint64_t d2, uint64_t d3) {
    wgmma_rs_n40_tb_h(o, p[0], d0);
    wgmma_rs_n40_tb_h(o, p[1], d1);
    wgmma_rs_n40_tb_h(o, p[2], d2);
    wgmma_rs_n40_tb_h(o, p[3], d3);
}
#define QK_DESC(j) P.dtab[(j) * 6], P.dtab[(j) * 6 + 1]
#define PV_DESC(j) P.dtab[(j) * 6 + 2], P.dtab[(j) * 6 + 3], P.dtab[(j) * 6 + 4], P.dtab[(j) * 6 + 5]

__device__ __forceinline__ uint32_t f16_to_bf16_pair(uint32_t h) {
    const float2 f = __half22float2(*reinterpret_cast<const __half2*>(&h));
    return pack_bf16(f.x, f.y);
}

__device__ __forceinline__ const uint8_t* q_block(int t) {
    return reinterpret_cast<const uint8_t*>(g_qkv) + (size_t)(((t < 256 ? SLOT_QB : SLOT_QA) + ((t >> 3) & 31)) * SEQ + (t & 7) * 256) * 64;
}
__device__ __forceinline__ void load_kv_block(uint32_t dst, int t, int g, uint32_t bar) {
    const uint8_t* k = reinterpret_cast<const uint8_t*>(g_qkv) + (size_t)((t < 256 ? SLOT_KB : SLOT_KA + ((t >> 3) & 31)) * SEQ + g * 256) * 64;
    bulk_load(dst, k, 16384, bar);
    bulk_load(dst + A_V_OFF, k + (size_t)KV_STRIDE * SEQ * 64, 16384, bar);
}

__global__ void __launch_bounds__(NTHREADS, 1) fused_kernel(const __grid_constant__ Params P) {
    extern __shared__ __align__(1024) uint8_t smem_raw[];
    const uint32_t sbase = smem_u32(smem_raw);
    const uint32_t s_bar = sbase + OFF_BAR;
    const int tid = threadIdx.x, lane = tid & 31;
    const int warp = __shfl_sync(0xffffffffu, tid >> 5, 0), wg = warp >> 2, wq = warp & 3;
    const int cta = blockIdx.x;
    const bool kvcta = cta >= 128;
    const int kv_unit = cta >= 128 ? cta - 116 : (cta >= 104 && cta < 116 ? cta - 104 : -1);
    TS(0, 0);
    unsigned long long launch_no = 0;
    if (tid == 256) launch_no = atomicAdd(&g_launch, 1ull);
    if (warp == 9) {
        asm volatile("prefetch.global.L2 [%0];" :: "l"(P.p_wqkv + lane * 196608 + (cta & 7) * 128));
        asm volatile("prefetch.global.L2 [%0];" :: "l"(P.p_wq + lane * 65536 + (cta & 7) * 128));
        asm volatile("prefetch.global.L2 [%0];" :: "l"(P.p_xb + lane * 131072 + (cta & 7) * 128));
        if (TLB_XA) asm volatile("prefetch.global.L2 [%0];" :: "l"(P.p_xa + lane * 131072 + (cta & 7) * 128));
    }
    auto load_proj = [&](int it, int kb) {
        bool isA; int mblk, nblk;
        proj_tile(cta, it, isA, mblk, nblk);
        const uint32_t full = s_bar + B_GFULL + (kb & 3) * 8;
        mbar_expect_tx(full, G_STAGE_BYTES);
        const uint32_t sa = sbase + (kb & 3) * G_STAGE_BYTES;
        tma_load_2d(sa, isA ? &P.xa : &P.xb, full, kb * 64, mblk * 128);
        tma_load_3d(sa + G_A_BYTES, isA ? &P.wqkv : &P.wq, full, 0, kb * 64, nblk * 4);
    };
    auto load_unit = [&](int kb) {
        const uint32_t full = s_bar + B_KVFULL + (kb & 7) * 8;
        mbar_expect_tx(full, KV_STAGE_BYTES);
        const uint32_t sa = sbase + (kb & 7) * KV_STAGE_BYTES;
        tma_load_2d(sa, &P.xb, full, kb * 64, kv_unit * 128);
        tma_load_2d(sa + G_A_BYTES, &P.wk, full, 0, kb * 64);
        tma_load_2d(sa + G_A_BYTES + 4096, &P.wv, full, 0, kb * 64);
    };
    if (tid == 384) {
        for (int s = 0; s < G_STAGES; s++) mbar_init(s_bar + B_GFULL + s * 8, 1);
        for (int s = 0; s < KV_STAGES; s++) mbar_init(s_bar + B_KVFULL + s * 8, 1);
        fence_barrier_init();
        if (kv_unit >= 0) { for (int s = 0; s < KV_STAGES; s++) load_unit(s); }
        else { for (int s = 0; s < G_STAGES; s++) load_proj(0, s); }
    }
    if (warp == 10 && lane < 13) prefetch_map(&P.xa + lane);
    if (tid == 0) {
        if ((sbase & 0x3FFFFu) != SMEM_BASE) __trap();
        for (int s = 0; s < 4; s++) {
            mbar_init(s_bar + B_GEMPTY + s * 8, 8);
            mbar_init(s_bar + B_AFULL + s * 8, 1); mbar_init(s_bar + B_AEMPTY + s * 8, 16);
            mbar_init(s_bar + B_OFULL + s * 8, 1); mbar_init(s_bar + B_OEMPTY + s * 8, 8);
        }
        for (int s = 0; s < KV_STAGES; s++) mbar_init(s_bar + B_KVEMPTY + s * 8, 8);
        for (int s = 0; s < 2; s++) { mbar_init(s_bar + B_QFULL + s * 8, 1); mbar_init(s_bar + B_QEMPTY + s * 8, 16); }
        mbar_init(s_bar + B_REDO, 1);
        mbar_init(s_bar + B_EPI, kvcta ? 2 : 8);
        mbar_init(s_bar + B_EPOCH, 1);
        fence_barrier_init();
        *reinterpret_cast<uint4*>(smem_raw + OFF_BAR + S_REDO) = make_uint4(0u, 0u, 0x9A0E9A0Eu, 0u);
        *reinterpret_cast<uint32_t*>(smem_raw + OFF_BAR + S_PF) = 0u;
    }
    if (tid >= 64 && tid < 128) {
        *reinterpret_cast<uint4*>(smem_raw + OFF_ONES + (tid - 64) * 16) = make_uint4(0x3C00u, 0u, 0u, 0u);
        fence_proxy_async();
    }
    __syncthreads();

    auto load_q = [&](int t, int qb) {
        const bool isB = t < 256;
        const int head = (t >> 3) & 31;
        const uint32_t qf = s_bar + B_QFULL + qb * 8;
        mbar_expect_tx(qf, A_Q_BYTES + 16);
        bulk_load(sbase + A_OFF_Q + qb * A_Q_BYTES, q_block(t), A_Q_BYTES, qf);
        bulk_load(s_bar + S_INFO + qb * 16, &g_stat[isB ? 32 : head], 16, qf);
    };
    auto load_kv = [&](int t, int g) {
        const uint32_t full = s_bar + B_AFULL + (g & 3) * 8;
        mbar_expect_tx(full, A_KV_BYTES);
        load_kv_block(sbase + (g & 3) * G_STAGE_BYTES + G_A_BYTES, t, g, full);
    };
    auto load_out = [&](int prob, int mblk, int nblk, int kb) {
        const uint32_t full = s_bar + B_OFULL + (kb & 3) * 8;
        const uint32_t sa = sbase + (kb & 3) * G_STAGE_BYTES;
        mbar_expect_tx(full, G_STAGE_BYTES);
        tma_load_3d(sa + G_A_BYTES, prob ? &P.wob : &P.woa, full, 0, kb * 64, nblk * 4);
        tma_load_2d(sa, &P.o, full, kb * 64, prob * SEQ + mblk * 128);
    };

    [[maybe_unused]] int st_row = -1, st_slot = 0;
    if (wg >= 2) {
        if (tid == 256) {
            const uint32_t e = (uint32_t)(launch_no / NCTA);
            asm volatile("st.volatile.shared.u32 [%0], %1;" :: "r"(s_bar + S_EPOCH), "r"(e) : "memory");
            mbar_arrive(s_bar + B_EPOCH);
        }
        __syncwarp();
        reg_dealloc<32>();
        if (warp == 12) {
            if (lane == 0) {
                if (kv_unit >= 0) {
                    for (int kb = KV_STAGES; kb < 16; kb++) {
                        mbar_wait(s_bar + B_KVEMPTY + (kb & 7) * 8, 0);
                        load_unit(kb);
                    }
                    for (int s = 0; s < KV_STAGES; s++) mbar_wait(s_bar + B_KVEMPTY + s * 8, 1);
                    if (!kvcta) for (int s = 0; s < G_STAGES; s++) load_proj(0, s);
                }
                if (!kvcta) {
                    for (int u = G_STAGES; u < 32; u++) {
                        mbar_wait(s_bar + B_GEMPTY + (u & 3) * 8, ((u >> 2) & 1) ^ 1);
                        load_proj(u >> 4, u & 15);
                    }
                }
                const uint32_t epoch = get_epoch(s_bar);
                await(C_QB, N_QB, epoch);
                await(C_RDYB, N_RDYB, epoch);
                TSX(0, 5);
                fence_proxy_all();
                mbar_wait(s_bar + B_EPI, 0);
                load_q(cta, 0);
                TSX(3, 4);
                for (int s = 0; s < 4; s++) {
                    if (!kvcta) mbar_wait(s_bar + B_GEMPTY + s * 8, 1);
                    load_kv(cta, s);
                    if (s == 0) TSX(3, 5);
                    if (s == 2) TSX(3, 6);
                }
                TSX(0, 6);
            }
            __syncwarp();
        } else if (warp == 13 && !kvcta) {
        } else if (wg == 2 && kvcta) {
            const uint32_t epoch = get_epoch(s_bar);
            auto stat = [&](int slotK, int idx) {
                const uint4 a = __ldcg(reinterpret_cast<const uint4*>(&g_n2[slotK * 128 + lane * 4]));
                const uint4 b = __ldcg(reinterpret_cast<const uint4*>(&g_n2[(slotK + KV_STRIDE) * 128 + lane * 4]));
                const bool ok = kv_is_f16(a.x, false) && kv_is_f16(a.y, false) && kv_is_f16(a.z, false) && kv_is_f16(a.w, false) &&
                                kv_is_f16(b.x, true) && kv_is_f16(b.y, true) && kv_is_f16(b.z, true) && kv_is_f16(b.w, true);
                float kn2 = __uint_as_float(__reduce_max_sync(0xffffffffu, max(max(a.x, a.y), max(a.z, a.w))));
                if (!__all_sync(0xffffffffu, ok)) kn2 = INFINITY;
                float sum = (__uint_as_float(a.x) + __uint_as_float(a.y)) + (__uint_as_float(a.z) + __uint_as_float(a.w));
#pragma unroll
                for (int x = 16; x > 0; x >>= 1) sum += __shfl_xor_sync(0xffffffffu, sum, x);
                if (lane == 0) g_stat[idx] = make_float4(kn2, sum * (1.0f / (128.0f * 47.0f)), 0.f, 0.f);
            };
            if (cta == 128 && wq == 0) {
                if (lane == 0) await(C_KVB, N_KVB, epoch);
                __syncwarp();
                stat(SLOT_KB, 32);
                if (lane == 0) signal(C_RDYB);
            }
            if (lane == 0) await(C_A, N_A, epoch);
            __syncwarp();
            for (int i = 0; i < 2; i++) {
                const int head = (cta - 128) * 8 + wq * 2 + i;
                stat(SLOT_KA + head, head);
            }
            if (lane == 0) signal(C_RDYA);
        }
        named_bar_sync(6 + wg, 256);
        reg_alloc<128>();
        TST(256, 3, 7);
    } else {
        reg_alloc<224>();
        auto release_regs = [&]() {
            named_bar_sync(4 + wg, 128);
            reg_dealloc<128>();
            asm volatile("bar.arrive %0, 256;" :: "r"(8 + wg) : "memory");
        };
        if (kv_unit >= 0) {
            const uint32_t epi = sbase + OFF_EPI + wg * 16384;
            const int srow = wq * 16 + (lane & 7);
            const uint32_t st_off0 = srow * 64 + (((lane >> 3) ^ ((srow >> 1) & 3)) << 4);
            float acc[32];
#pragma unroll
            for (int i = 0; i < 32; i++) acc[i] = 0.f;
#pragma unroll 1
            for (int kb = 0; kb < 16; kb++) {
                const int stage = kb & 7;
                mbar_wait(s_bar + B_KVFULL + stage * 8, kb >> 3);
                const uint32_t sa = sbase + stage * KV_STAGE_BYTES;
                const uint64_t da = make_desc(sa + wg * 8192, 16, 1024, 1);
                const uint64_t db = make_desc(sa + G_A_BYTES, 4096, 512, 2);
                wg_fence();
#pragma unroll
                for (int kk = 0; kk < 4; kk++) wgmma_ss_n64_tb(acc, da + kk * 2, db + kk * 64);
                wg_commit();
                if (kb > 0) {
                    wg_wait<1>();
                    if (lane == 0) mbar_arrive(s_bar + B_KVEMPTY + ((kb - 1) & 7) * 8);
                }
            }
            wg_wait<0>();
            fence_regs(acc);
            if (lane == 0) mbar_arrive(s_bar + B_KVEMPTY + 7 * 8);
            const int row0 = kv_unit * 128 + wg * 64;
            uint32_t n2[2];
            slot_norms<2>(acc, n2, SLOT_KB, SLOT_VB - SLOT_KB, (row0 >> 4) + wq, lane);
#pragma unroll
            for (int s = 0; s < 2; s++) {
                uint32_t pk[8];
                if (kv_is_f16(n2[s], s != 0)) pack_slot<true>(pk, &acc[s * 16], 1.0f);
                else pack_slot<false>(pk, &acc[s * 16], 1.0f);
                stage_slot(epi + s * 4096 + st_off0, pk);
            }
            fence_proxy_async();
            named_bar_sync(1 + wg, 128);
            if (wq == 0 && lane == 0) {
                tma_store_3d(&P.qkv_st1, epi, 0, row0 >> 1, SLOT_KB);
                tma_store_3d(&P.qkv_st1, epi + 4096, 0, row0 >> 1, SLOT_VB);
                bulk_commit();
                bulk_wait<0>();
                signal(C_KVB);
                if (kvcta) mbar_arrive(s_bar + B_EPI);
            }
            named_bar_sync(1 + wg, 128);
            TS(0, 7);
        }
        if (!kvcta) {
            const uint32_t st_off = (lane & 7) * 64 + (((lane >> 3) ^ ((lane >> 1) & 3)) << 4);
            float acc[128];
            uint32_t pk[64];
            int row0 = 0, slot0 = 0;
            auto finish = [&](int it) {
                bool isA; int mblk, nblk;
                proj_tile(cta, it, isA, mblk, nblk);
                slot0 = isA ? nblk * 8 + (nblk >= 8 ? 1 : 0) : SLOT_QB + nblk * 8;
                row0 = mblk * 128 + warp * 16;
                if (slot0 < SLOT_KA || slot0 >= SLOT_QB) {
#pragma unroll
                    for (int s = 0; s < 8; s++) pack_slot<false>(&pk[s * 8], &acc[s * 16], QSCALE);
                } else {
                    const bool isV = slot0 >= SLOT_VA;
                    uint32_t n2[8];
                    slot_norms<8>(acc, n2, slot0, 1, row0 >> 4, lane);
#pragma unroll
                    for (int s = 0; s < 8; s++) {
                        if (kv_is_f16(n2[s], isV)) pack_slot<true>(&pk[s * 8], &acc[s * 16], 1.0f);
                        else pack_slot<false>(&pk[s * 8], &acc[s * 16], 1.0f);
                    }
                }
            };
            gemm_tile<false>(acc, sbase, s_bar + B_GFULL, s_bar + B_GEMPTY, wg, lane, true, [&](int kb) { if (kb == 0) TS(0, 1); });
            TS(0, 2);
            KS(64);
            finish(0);
            KS(65);
            auto event = [&](int r) {
                const uint32_t buf = sbase + OFF_EPI + warp * 4096 + (r & 1) * 2048;
                if (r >= 2) { if (lane == 0) bulk_wait_read<1>(); __syncwarp(); }
                stage_slot(buf + st_off, &pk[r * 16]);
                stage_slot(buf + 1024 + st_off, &pk[r * 16 + 8]);
                fence_proxy_async();
                __syncwarp();
                if (lane == 0) { tma_store_3d(&P.qkv_st, buf, 0, row0 >> 1, slot0 + r * 2); bulk_commit(); }
            };
            gemm_tile<true>(acc, sbase, s_bar + B_GFULL, s_bar + B_GEMPTY, wg, lane, true, [&](int kb) {
                const int e0 = kb - EV0, e1 = kb - EV0 - EVW;
                if (wg == 0) { if (e0 >= 0 && e0 % EVS == 0 && e0 / EVS < 4) event(e0 / EVS); }
                else { if (e1 >= 0 && e1 % EVS == 0 && e1 / EVS < 4) event(e1 / EVS); }
                if (kb == SIG_KB && lane == 0) {
                    bulk_wait<0>();
                    signal(cta < 64 ? C_QB : C_A);
                    mbar_arrive(s_bar + B_EPI);
                }
            }, 32);
            TS(0, 3);
            TST(128, 3, 0);
            KS(66);
            finish(1);
            TST(128, 3, 1);
            release_regs();
            KS(67);
#pragma unroll
            for (int c = 0; c < 4; c++) {
                const uint32_t buf = sbase + c * G_STAGE_BYTES + warp * 2048;
                stage_slot(buf + st_off, &pk[c * 16]);
                stage_slot(buf + 1024 + st_off, &pk[c * 16 + 8]);
            }
            fence_proxy_async();
            __syncwarp();
            TST(128, 3, 2);
            st_row = row0 >> 1; st_slot = slot0;
            TST(128, 3, 3);
            KS(68);
            TS(0, 4);
        } else {
            release_regs();
        }
    }

    TS(1, 0);
    auto refill = [&](int it, int g) {
        int t = cta + it * NCTA;
        if (g >= 8) {
            g -= 8; t += NCTA; it++;
            if (t >= A_TILES) {
                const int n_out = cta < 100 ? 1 : (cta < 116 ? 0 : 1);
                if (n_out != 0) {
                    int prob, mblk, nblk;
                    out_tile(cta, 0, prob, mblk, nblk);
                    uint32_t cnt;
                    asm volatile("ld.volatile.shared.u32 %0, [%1];" : "=r"(cnt) : "r"(s_bar + S_OCNT + g * 4) : "memory");
                    if ((int)(cnt - (get_epoch(s_bar) + 1) * N_O) >= 0) {
                        mbar_wait(s_bar + B_AEMPTY + g * 8, 1);
                        load_out(prob, mblk, nblk, g);
                        asm volatile("st.volatile.shared.u8 [%0], %1;" :: "r"(s_bar + S_PF + g), "r"(1u) : "memory");
                    }
                }
                return;
            }
            if (t >= 256 && t - NCTA < 256) { await(C_RDYA, N_RDYA, get_epoch(s_bar)); fence_proxy_all(); }
        } else if (it == 0 && g < 4) return;
        if (g == 0) {
            mbar_wait(s_bar + B_QEMPTY + (it & 1) * 8, ((it >> 1) & 1) ^ 1);
            load_q(t, it & 1);
        }
        mbar_wait(s_bar + B_AEMPTY + (g & 3) * 8, ((g >> 2) & 1) ^ 1);
        if (g == 5 && t + NCTA >= A_TILES) {
            asm volatile("mbarrier.expect_tx.relaxed.cta.shared::cta.b64 [%0], 64;" :: "r"(s_bar + B_AFULL + 8) : "memory");
            bulk_load(s_bar + S_OCNT, &g_cnt[C_O + (cta >= 36 && cta < 100 ? 0 : 32)], 64, s_bar + B_AFULL + 8);
        }
        load_kv(t, g);
    };
    auto load_qfrag = [&](uint32_t qbuf, uint32_t (&q0)[4], uint32_t (&q1)[4]) {
        const int r = wg * 64 + wq * 16 + (lane & 7) + ((lane >> 3) & 1) * 8;
        const uint32_t base = qbuf + r * 64;
        const uint32_t sw = (r >> 1) & 3;
        ldmatrix_x4(base + ((((lane >> 4)) ^ sw) << 4), q0);
        ldmatrix_x4(base + (((2 + (lane >> 4)) ^ sw) << 4), q1);
    };
    auto epilogue = [&](const float (&o)[20], float l0, float l1, int t, int qb) {
        const uint32_t s_ostage = sbase + A_OFF_Q + qb * A_Q_BYTES + warp * 1024;
        const float r0 = 1.0f / l0, r1 = 1.0f / l1;
        const int r = lane & 7;
        const uint32_t a0 = s_ostage + r * 64 + (((lane >> 3) ^ ((r >> 1) & 3)) << 4);
        stmatrix_x4(a0, pack_bf16(o[0] * r0, o[1] * r0), pack_bf16(o[4] * r0, o[5] * r0),
                    pack_bf16(o[8] * r0, o[9] * r0), pack_bf16(o[12] * r0, o[13] * r0));
        stmatrix_x4(a0 + 512, pack_bf16(o[2] * r1, o[3] * r1), pack_bf16(o[6] * r1, o[7] * r1),
                    pack_bf16(o[10] * r1, o[11] * r1), pack_bf16(o[14] * r1, o[15] * r1));
        fence_proxy_async();
        __syncwarp();
        if (lane == 0) {
            tma_store_2d(&P.o_st, s_ostage, ((t >> 3) & 31) * 32, (t < 256 ? SEQ : 0) + (t & 7) * 256 + wg * 64 + wq * 16);
            bulk_commit();
        }
    };
    auto o_counter = [&](int t) { return C_O + (t < 256 ? 32 : 0) + ((t >> 4) & 15); };

    int pend = (wg < 2 && !kvcta) ? C_A : -1;
    {
        int it = 0;
        for (int t = cta; t < A_TILES; t += NCTA, it++) {
            const int qb = it & 1;
            mbar_wait(s_bar + B_QFULL + qb * 8, (it >> 1) & 1);
            if (it == 0) { TS(1, 4); TST(256, 1, 5); }
            if (it == 2 && warp == 5 && lane < 16) {
                const int u = cta * 16 + lane;
                if (u < 2048) l2_prefetch((u < 1024 ? P.p_woa : P.p_wob - (size_t)1024 * 2048) + (size_t)u * 2048, 2048);
            }
            uint32_t q0[4], q1[4];
            float kn2, sk2;
            uint32_t kb;
            load_qfrag(sbase + A_OFF_Q + qb * A_Q_BYTES, q0, q1);
            asm volatile("ld.shared.v2.f32 {%0, %1}, [%2];" : "=f"(kn2), "=f"(sk2) : "r"(s_bar + S_INFO + qb * 16) : "memory");
            asm volatile("ld.volatile.shared.u32 %0, [%1];" : "=r"(kb) : "r"(s_bar + S_KB));
            float qa = 0.f, qc = 0.f;
#pragma unroll
            for (int i = 0; i < 4; i++) {
                const uint32_t u0 = q0[i], u1 = q1[i];
                const float x0 = __uint_as_float(u0 << 16), x1 = __uint_as_float(u0 & 0xffff0000u);
                const float y0 = __uint_as_float(u1 << 16), y1 = __uint_as_float(u1 & 0xffff0000u);
                const float ss = x0 * x0 + x1 * x1 + y0 * y0 + y1 * y1;
                if (i & 1) qc += ss; else qa += ss;
                q0[i] = pack_f16(x0, x1); q1[i] = pack_f16(y0, y1);
            }
            uint32_t s[2][16], oh[10], p[2][4][4];
#pragma unroll
            for (int i = 0; i < 10; i++) oh[i] = 0;
            fence_regs_u(oh);
            mbar_wait(s_bar + B_AFULL, 0);
            if (it == 0) { TS(1, 1); TST(256, 1, 6); }
            wg_fence();
            issue_qk_h(s[0], q0, q1, QK_DESC(0));
            wg_commit();
            issue_qk_h(s[1], q0, q1, QK_DESC(1));
            wg_commit();
            qa += __shfl_xor_sync(0xffffffffu, qa, 1); qc += __shfl_xor_sync(0xffffffffu, qc, 1);
            qa += __shfl_xor_sync(0xffffffffu, qa, 2); qc += __shfl_xor_sync(0xffffffffu, qc, 2);
            bool ok = (qa * kn2 <= FAST_BOUND2) && (qc * kn2 <= FAST_BOUND2) && (qa <= 16777216.f) && (qc <= 16777216.f);
            wg_wait<1>();
            fence_regs_u(s[0]);
            uint32_t nc[2], M[2];
            {
                uint32_t m0 = s[0][0], m1 = s[0][1], a0 = s[0][0], a1 = s[0][1];
#pragma unroll
                for (int i = 1; i < 8; i++) {
                    m0 = hmax2(m0, s[0][2 * i]); m1 = hmax2(m1, s[0][2 * i + 1]);
                    a0 = hadd2(a0, s[0][2 * i]); a1 = hadd2(a1, s[0][2 * i + 1]);
                }
                uint32_t m = hmax2(__byte_perm(m0, m1, 0x5410), __byte_perm(m0, m1, 0x7632));
                uint32_t a = hadd2(__byte_perm(a0, a1, 0x5410), __byte_perm(a0, a1, 0x7632));
                m = hmax2(m, __shfl_xor_sync(0xffffffffu, m, 1)); a = hadd2(a, __shfl_xor_sync(0xffffffffu, a, 1));
                m = hmax2(m, __shfl_xor_sync(0xffffffffu, m, 2)); a = hadd2(a, __shfl_xor_sync(0xffffffffu, a, 2));
                const float2 mf = __half22float2(*reinterpret_cast<const __half2*>(&m));
                const float2 af = __half22float2(*reinterpret_cast<const __half2*>(&a));
                const float c0 = row_shift(mf.x, af.x * (1.0f / 64.0f), qa * sk2);
                const float c1 = row_shift(mf.y, af.y * (1.0f / 64.0f), qc * sk2);
                nc[0] = pack_f16(0.5f - c0, 0.5f - c0); nc[1] = pack_f16(0.5f - c1, 0.5f - c1);
                M[0] = pack_f16(1536.0f - c0, 1536.0f - c0); M[1] = pack_f16(1536.0f - c1, 1536.0f - c1);
            }
            ExpPackH<0>::run(s[0], p[0], nc, M, kb);
            wg_wait<0>();
            fence_regs_u(s[1]);
#pragma unroll 1
            for (int h = 0; h < 2; h++) {
#pragma unroll
                for (int j = 0; j < 16; j++) {
                    const int jn = (j + 2) & 15;
                    if (j == 15 && h == 1) {
                        wg_fence();
                        issue_pv_h(oh, p[1], PV_DESC(15));
                        wg_commit();
                        wg_wait<0>();
                        fence_regs_u(oh);
                        if (lane == 0) mbar_arrive(s_bar + B_AEMPTY + 3 * 8);
                    } else {
                        if (j == 14 && h == 1) {
                            wg_fence();
                            issue_pv_h(oh, p[0], PV_DESC(14));
                        } else {
                            if ((j & 3) == 2) mbar_wait(s_bar + B_AFULL + (jn >> 2) * 8, j == 14 ? 1 : h);
                            wg_fence();
                            issue_qk_h(s[j & 1], q0, q1, QK_DESC(jn));
                            issue_pv_h(oh, p[j & 1], PV_DESC(j));
                        }
                        wg_commit();
                        if ((j & 3) == RF_STEP) {
                            if (tid == (j >> 2) * 128) refill(it, h * 4 + (j >> 2) + 2);
                            __syncwarp();
                        }
                        if (j == ST_STEP && h == 0 && lane == 0 && st_row >= 0) {
#pragma unroll
                            for (int c = 0; c < 4; c++) tma_store_3d(&P.qkv_st, sbase + c * G_STAGE_BYTES + warp * 2048, 0, st_row, st_slot + c * 2);
                            bulk_commit();
                            st_row = -1;
                        }
                        if (j == SIG_STEP && h == 0 && lane == 0) {
                            bulk_wait<0>();
                            if (pend >= 0) signal(pend);
                            pend = -1;
                            if (it > 0) mbar_arrive(s_bar + B_QEMPTY + (qb ^ 1) * 8);
                        }
                        wg_wait<1>();
                        fence_regs_u(s[(j + 1) & 1]);
                        if ((j & 3) == 0 && lane == 0 && (j > 0 || h > 0)) mbar_arrive(s_bar + B_AEMPTY + (((j >> 2) + 3) & 3) * 8);
                        ExpPackH<0>::run(s[(j + 1) & 1], p[(j + 1) & 1], nc, M, kb);
                        if (j == 15) {
                            wg_wait<0>(); fence_regs_u(oh); fence_regs_u(s[1]);
                        }
                    }
                }
            }
            float o[20];
#pragma unroll
            for (int i = 0; i < 10; i++) { const float2 f = __half22float2(*reinterpret_cast<const __half2*>(&oh[i])); o[2 * i] = f.x; o[2 * i + 1] = f.y; }
            const float l0 = __shfl_sync(0xffffffffu, o[16], lane & ~3);
            const float l1 = __shfl_sync(0xffffffffu, o[18], lane & ~3);
            ok = ok && l0 >= 40.f && l0 <= 65504.f && l1 >= 40.f && l1 <= 65504.f;
#pragma unroll
            for (int i = 0; i < 16; i++) ok = ok && fabsf(o[i]) <= 65504.f;
            if (__all_sync(0xffffffffu, ok)) { epilogue(o, l0, l1, t, qb); pend = o_counter(t); }
            else if (lane == 0) asm volatile("red.shared.or.b32 [%0], %1;" :: "r"(s_bar + S_REDO + (it >> 1) * 4), "r"(1u << ((it & 1) * 16 + warp)) : "memory");
        }
    }
    TS(1, 2);
    __syncthreads();

    uint32_t redo_lo, redo_hi, pf;
    asm volatile("ld.volatile.shared.v2.u32 {%0, %1}, [%2];" : "=r"(redo_lo), "=r"(redo_hi) : "r"(s_bar + S_REDO) : "memory");
    asm volatile("ld.volatile.shared.u32 %0, [%1];" : "=r"(pf) : "r"(s_bar + S_PF) : "memory");
    if ((redo_lo | redo_hi) != 0) {
        if (lane == 0 && pend >= 0) { bulk_wait<0>(); signal(pend); pend = -1; }
        if (tid < 64) *reinterpret_cast<uint4*>(smem_raw + OFF_ONES + tid * 16) = make_uint4(0x3F80u, 0u, 0u, 0u);
        const uint32_t rb = s_bar + B_REDO;
        uint32_t par = 0;
#pragma unroll 1
        for (int it = 0; it < 4; it++) {
            const uint32_t m = ((it < 2 ? redo_lo : redo_hi) >> ((it & 1) * 16)) & 0xffffu;
            if (m == 0) continue;
            const bool mine = ((m >> (wg * 4)) & 15u) != 0;
            const int t = cta + it * NCTA;
            const int slotK = t < 256 ? SLOT_KB : SLOT_KA + ((t >> 3) & 31);
            __syncthreads();
            if (tid == 0) {
                mbar_expect_tx(rb, A_Q_BYTES);
                bulk_load(sbase + A_OFF_Q, q_block(t), A_Q_BYTES, rb);
            }
            mbar_wait(rb, par); par ^= 1;
            uint32_t q0[4], q1[4];
            load_qfrag(sbase + A_OFF_Q, q0, q1);
            float m0 = -INFINITY, m1 = -INFINITY;
            float o[20];
#pragma unroll
            for (int i = 0; i < 20; i++) o[i] = 0.f;
            fence_regs(o);
#pragma unroll 1
            for (int st = 0; st < 8; st++) {
                __syncthreads();
                if (tid == 0) {
                    mbar_expect_tx(rb, A_KV_BYTES);
                    load_kv_block(sbase + a_koff(12), t, st, rb);
                }
                mbar_wait(rb, par); par ^= 1;
#pragma unroll 1
                for (int i = 0; i < 4; i++) {
                    const int chunk = tid + i * NTHREADS;
                    const bool is_v = chunk >= 1024;
                    const int grp = st * 16 + ((chunk & 1023) >> 6);
                    const uint32_t n2 = __float_as_uint(__ldcg(&g_n2[(slotK + (is_v ? KV_STRIDE : 0)) * 128 + grp]));
                    if (kv_is_f16(n2, is_v)) {
                        uint4* ptr = reinterpret_cast<uint4*>(smem_raw + a_koff(12) + chunk * 16);
                        uint4 v = *ptr;
                        v.x = f16_to_bf16_pair(v.x); v.y = f16_to_bf16_pair(v.y); v.z = f16_to_bf16_pair(v.z); v.w = f16_to_bf16_pair(v.w);
                        *ptr = v;
                    }
                }
                fence_proxy_async();
                __syncthreads();
                if (mine) {
#pragma unroll 1
                    for (int sub = 12; sub < 16; sub++) {
                        float s[32];
                        wg_fence();
                        wgmma_rs_n64_z(s, q0, P.dtab[sub * 6]);
                        wgmma_rs_n64(s, q1, P.dtab[sub * 6 + 1]);
                        wg_commit();
                        wg_wait<0>();
                        fence_regs(s);
                        float t0 = m0, t1 = m1;
#pragma unroll
                        for (int i = 0; i < 8; i++) {
                            t0 = fmaxf(t0, fmaxf(s[4 * i], s[4 * i + 1]));
                            t1 = fmaxf(t1, fmaxf(s[4 * i + 2], s[4 * i + 3]));
                        }
                        t0 = fmaxf(t0, __shfl_xor_sync(0xffffffffu, t0, 1)); t1 = fmaxf(t1, __shfl_xor_sync(0xffffffffu, t1, 1));
                        t0 = fmaxf(t0, __shfl_xor_sync(0xffffffffu, t0, 2)); t1 = fmaxf(t1, __shfl_xor_sync(0xffffffffu, t1, 2));
                        const float al0 = ex2_mufu(m0 - t0), al1 = ex2_mufu(m1 - t1);
                        m0 = t0; m1 = t1;
#pragma unroll
                        for (int i = 0; i < 5; i++) { o[4 * i] *= al0; o[4 * i + 1] *= al0; o[4 * i + 2] *= al1; o[4 * i + 3] *= al1; }
                        uint32_t p[4][4];
#pragma unroll
                        for (int kk = 0; kk < 4; kk++) {
                            p[kk][0] = pack_bf16(ex2_mufu(s[kk * 8 + 0] - m0), ex2_mufu(s[kk * 8 + 1] - m0));
                            p[kk][1] = pack_bf16(ex2_mufu(s[kk * 8 + 2] - m1), ex2_mufu(s[kk * 8 + 3] - m1));
                            p[kk][2] = pack_bf16(ex2_mufu(s[kk * 8 + 4] - m0), ex2_mufu(s[kk * 8 + 5] - m0));
                            p[kk][3] = pack_bf16(ex2_mufu(s[kk * 8 + 6] - m1), ex2_mufu(s[kk * 8 + 7] - m1));
                        }
                        wg_fence();
                        wgmma_rs_n40_tb(o, p[0], P.dtab[sub * 6 + 2]);
                        wgmma_rs_n40_tb(o, p[1], P.dtab[sub * 6 + 3]);
                        wgmma_rs_n40_tb(o, p[2], P.dtab[sub * 6 + 4]);
                        wgmma_rs_n40_tb(o, p[3], P.dtab[sub * 6 + 5]);
                        wg_commit();
                        wg_wait<0>();
                        fence_regs(o);
                    }
                }
            }
            if (mine) {
                const float l0 = __shfl_sync(0xffffffffu, o[16], lane & ~3);
                const float l1 = __shfl_sync(0xffffffffu, o[18], lane & ~3);
                if ((m >> warp) & 1) {
                    epilogue(o, l0, l1, t, 0);
                    if (lane == 0) { bulk_wait<0>(); signal(o_counter(t)); }
                }
            }
        }
        __syncthreads();
    }
    TS(1, 3);

    const int n_out = out_tiles(cta);
    auto flush_o = [&]() {
        if (lane == 0) {
            bulk_wait<0>();
            if (pend >= 0) signal(pend);
        }
    };
    if (wg >= 2) {
        reg_dealloc<32>();
        if (warp == 12 && n_out > 0) {
            const uint32_t target = (get_epoch(s_bar) + 1) * N_O;
            uint32_t cnt;
            asm volatile("ld.volatile.shared.u32 %0, [%1];" : "=r"(cnt) : "r"(s_bar + S_OCNT + (lane & 15) * 4) : "memory");
            uint32_t rdy = __ballot_sync(0xffffffffu, (int)(cnt - target) >= 0);
            bool flushed = false;
            int use = 0;
            for (int i = 0; i < n_out; i++) {
                int prob, mblk, nblk;
                out_tile(cta, i, prob, mblk, nblk);
                for (int kb = 0; kb < 16; kb++, use++) {
                    if (!flushed && (use == 4 || !((rdy >> kb) & 1))) { flush_o(); flushed = true; }
                    if (use < 2 && ((pf >> (use * 8)) & 1)) continue;
                    if (!((rdy >> kb) & 1)) {
                        const uint32_t t0 = (uint32_t)clock();
                        while (true) {
                            const uint32_t v = ld_acquire(C_O + prob * 32 + (lane & 15));
                            rdy = __ballot_sync(0xffffffffu, (int)(v - target) >= 0);
                            if (((rdy >> kb) & 1) || __any_sync(0xffffffffu, (uint32_t)clock() - t0 > 0x0fffffffu)) break;
                            __nanosleep(64);
                        }
                        __syncwarp();
                        fence_proxy_all();
                    }
                    if (lane == 0) {
                        if (use >= 4) mbar_wait(s_bar + B_OEMPTY + (kb & 3) * 8, ((use >> 2) & 1) ^ 1);
                        load_out(prob, mblk, nblk, kb);
                    }
                    __syncwarp();
                }
            }
        } else {
            flush_o();
        }
    } else if (n_out == 0) {
        flush_o();
    } else {
        reg_alloc<224>();
        for (int i = 0; i < n_out; i++) {
            int prob, mblk, nblk;
            out_tile(cta, i, prob, mblk, nblk);
            float acc[128];
            gemm_tile<false>(acc, sbase, s_bar + B_OFULL, s_bar + B_OEMPTY, wg, lane, false, [&](int kb) {
                if (kb == 0 && i == 0) TS(2, 1);
                if (kb == FLUSH_KB && i == 0) flush_o();
            });
            TS(2, 2);
            const uint32_t st_off = warp * 2048 + (lane & 7) * 128;
#pragma unroll
            for (int c = 0; c < 4; c++) {
#pragma unroll
                for (int h = 0; h < 2; h++) {
                    const float* v16 = &acc[(c * 8 + h * 4) * 4];
                    const uint32_t ch = (uint32_t)(h * 4 + (lane >> 3));
                    const uint32_t a0 = sbase + c * G_STAGE_BYTES + st_off + ((ch ^ (lane & 7)) << 4);
                    stmatrix_x4(a0, pack_bf16(v16[0], v16[1]), pack_bf16(v16[4], v16[5]),
                                pack_bf16(v16[8], v16[9]), pack_bf16(v16[12], v16[13]));
                    stmatrix_x4(a0 + 8 * 128, pack_bf16(v16[2], v16[3]), pack_bf16(v16[6], v16[7]),
                                pack_bf16(v16[10], v16[11]), pack_bf16(v16[14], v16[15]));
                }
                if (c & 1) {
                    fence_proxy_async();
                    __syncwarp();
                    if (lane == 0) {
                        const int row0 = mblk * 128 + warp * 16;
                        const int col0 = prob * DM + nblk * 256;
                        tma_store_2d(&P.out_st, sbase + (c - 1) * G_STAGE_BYTES + warp * 2048, col0 + (c - 1) * 64, row0);
                        tma_store_2d(&P.out_st, sbase + c * G_STAGE_BYTES + warp * 2048, col0 + c * 64, row0);
                        bulk_commit();
                    }
                }
            }
            TS(2, 3);
            if (lane == 0) {
                if (i + 1 < n_out) {
                    bulk_wait_read<0>();
                    for (int s = 0; s < 4; s++) mbar_arrive(s_bar + B_OEMPTY + s * 8);
                } else {
                    bulk_wait<0>();
                }
            }
            __syncwarp();
            TS(2, 4);
        }
    }
}

typedef CUresult (*EncodeFn)(CUtensorMap*, CUtensorMapDataType, cuuint32_t, void*, const cuuint64_t*, const cuuint64_t*,
                             const cuuint32_t*, const cuuint32_t*, CUtensorMapInterleave, CUtensorMapSwizzle,
                             CUtensorMapL2promotion, CUtensorMapFloatOOBfill);

void make_map(EncodeFn enc, CUtensorMap* m, const void* ptr, int rank, const uint64_t* dims, const uint64_t* strides_bytes,
              const uint32_t* box, CUtensorMapSwizzle swz) {
    cuuint64_t gd[4], gs[3];
    cuuint32_t bx[4], es[4] = {1, 1, 1, 1};
    for (int i = 0; i < rank; i++) { gd[i] = dims[i]; bx[i] = box[i]; }
    for (int i = 0; i < rank - 1; i++) gs[i] = strides_bytes[i];
    enc(m, CU_TENSOR_MAP_DATA_TYPE_BFLOAT16, rank, const_cast<void*>(ptr), gd, gs, bx, es, CU_TENSOR_MAP_INTERLEAVE_NONE, swz,
        CU_TENSOR_MAP_L2_PROMOTION_L2_256B, CU_TENSOR_MAP_FLOAT_OOB_FILL_NONE);
}

void map_kmajor(EncodeFn enc, CUtensorMap* m, const void* p, uint64_t rows, uint64_t cols, uint32_t box_rows) {
    uint64_t d[2] = {cols, rows}, s[1] = {cols * 2};
    uint32_t b[2] = {64, box_rows};
    make_map(enc, m, p, 2, d, s, b, CU_TENSOR_MAP_SWIZZLE_128B);
}
void map_weight(EncodeFn enc, CUtensorMap* m, const void* p, uint64_t K, uint64_t N) {
    uint64_t d[3] = {64, K, N / 64}, s[2] = {N * 2, 128};
    uint32_t b[3] = {64, 64, 4};
    make_map(enc, m, p, 3, d, s, b, CU_TENSOR_MAP_SWIZZLE_128B);
}

}

extern "C" void kernel_launch(void* const* d_in, const int* in_sizes, int n_in, void* d_out, int out_size) {
    (void)in_sizes; (void)n_in; (void)out_size;
    static EncodeFn enc = nullptr;
    static void* p_qkv = nullptr;
    static void* p_o = nullptr;
    if (!enc) {
        void* fn = nullptr;
        cudaDriverEntryPointQueryResult qr;
        cudaGetDriverEntryPoint("cuTensorMapEncodeTiled", &fn, cudaEnableDefault, &qr);
        enc = (EncodeFn)fn;
        cudaGetSymbolAddress(&p_qkv, g_qkv);
        cudaGetSymbolAddress(&p_o, g_o);
        cudaFuncSetAttribute(fused_kernel, cudaFuncAttributeMaxDynamicSharedMemorySize, SMEM_BYTES);
    }
    const void* A_x = d_in[0]; const void* A_wqkv = d_in[1]; const void* A_wo = d_in[2];
    const void* B_x = d_in[3]; const void* B_wq = d_in[4]; const void* B_wk = d_in[5];
    const void* B_wv = d_in[6]; const void* B_wo = d_in[7];

    Params pp;
    map_kmajor(enc, &pp.xa, A_x, SEQ, DM, 128);
    map_kmajor(enc, &pp.xb, B_x, SEQ, DM, 128);
    map_weight(enc, &pp.wqkv, A_wqkv, DM, 3 * DM);
    map_weight(enc, &pp.wq, B_wq, DM, DM);
    {
        uint64_t d[2] = {32, DM}, s[1] = {64};
        uint32_t b[2] = {32, 64};
        make_map(enc, &pp.wk, B_wk, 2, d, s, b, CU_TENSOR_MAP_SWIZZLE_64B);
        make_map(enc, &pp.wv, B_wv, 2, d, s, b, CU_TENSOR_MAP_SWIZZLE_64B);
    }
    {
        uint64_t d[3] = {64, SEQ / 2, NSLOT}, s[2] = {128, (uint64_t)SEQ * 64};
        uint32_t b[3] = {64, 8, 2};
        make_map(enc, &pp.qkv_st, p_qkv, 3, d, s, b, CU_TENSOR_MAP_SWIZZLE_NONE);
        uint32_t b1[3] = {64, 32, 1};
        make_map(enc, &pp.qkv_st1, p_qkv, 3, d, s, b1, CU_TENSOR_MAP_SWIZZLE_NONE);
        uint64_t d2[2] = {DM, 2 * SEQ}, s2[1] = {DM * 2};
        uint32_t b2[2] = {32, 16};
        make_map(enc, &pp.o_st, p_o, 2, d2, s2, b2, CU_TENSOR_MAP_SWIZZLE_64B);
        for (int j = 0; j < 16; j++) {
            for (int i = 0; i < 2; i++) pp.dtab[j * 6 + i] = a_kdesc(j, i);
            for (int i = 0; i < 4; i++) pp.dtab[j * 6 + 2 + i] = a_vdesc(j, i);
        }
    }
    map_kmajor(enc, &pp.o, p_o, 2 * SEQ, DM, 128);
    map_weight(enc, &pp.woa, A_wo, DM, DM);
    map_weight(enc, &pp.wob, B_wo, DM, DM);
    {
        uint64_t d[2] = {2 * DM, SEQ}, s[1] = {2 * DM * 2};
        uint32_t b[2] = {64, 16};
        make_map(enc, &pp.out_st, d_out, 2, d, s, b, CU_TENSOR_MAP_SWIZZLE_128B);
    }
    pp.p_xa = (const uint8_t*)A_x; pp.p_woa = (const uint8_t*)A_wo; pp.p_wob = (const uint8_t*)B_wo;
    pp.p_wqkv = (const uint8_t*)A_wqkv; pp.p_wq = (const uint8_t*)B_wq; pp.p_xb = (const uint8_t*)B_x;
    fused_kernel<<<NCTA, NTHREADS, SMEM_BYTES, cudaStreamPerThread>>>(pp);
}
```
